```python
import torch

def _softmax(x, axis=-1):
    return torch.softmax(x, dim=axis)
def _gelu(x):
    return torch.nn.functional.gelu(x, approximate="tanh")
def _silu(x):
    return torch.nn.functional.silu(x)
def _sigmoid(x):
    return torch.sigmoid(x)
def _layernorm(x, axis=-1, eps=1e-5):
    m = x.mean(dim=axis, keepdim=True)
    v = x.var(dim=axis, keepdim=True, unbiased=False)
    return (x - m) / torch.sqrt(v + eps)
def _scatter_add(tgt, idx, src, axis=0):
    return tgt.clone().index_add_(axis, idx, src)
def _segment_sum(src, seg, n):
    out = torch.zeros((n,) + src.shape[1:], dtype=src.dtype)
    return out.index_add_(0, seg, src)
def _pad(x, pw):
    flat = tuple(v for pair in reversed(pw) for v in pair)
    return torch.nn.functional.pad(x, flat)

kernel_name = 'interleave_layers__ssm_conv_s4d__glu_gated_glu__prompt'

def setup_inputs():

    _w = (lambda a: (lambda t: t.to(torch.bfloat16) if t.is_floating_point() else t)(torch.as_tensor(a)))
    def _A_setup():
        Bsz, L, D, N = 1, 2048, 512, 128
        return {
            "u": _w((lambda *s: torch.randn(*s, dtype=torch.bfloat16) * 0.05)(Bsz, L, D)),
            "log_A_real": _w((lambda *s: torch.randn(*s, dtype=torch.bfloat16) * 3.2)(D, N) * 0.5),
            "A_imag": _w((lambda *s: torch.randn(*s, dtype=torch.bfloat16) * 0.1)(D, N) * 3.14),
            "C_real": _w((lambda *s: torch.randn(*s, dtype=torch.bfloat16) * 0.1)(D, N) / N ** 0.5),
            "C_imag": _w((lambda *s: torch.randn(*s, dtype=torch.bfloat16) * 0.1)(D, N) / N ** 0.5),
            "log_dt": _w((lambda *s: torch.randn(*s, dtype=torch.bfloat16) * 0.1)(D) * 0.5 - 4.0),
            "D_skip": _w((lambda *s: torch.randn(*s, dtype=torch.bfloat16) * 0.1)(D)),
        }
    _A_in = _A_setup()

    def _B_setup():
        B, S, D, F = 1, 2048, 512, 1376
        return {
            "x": _w((lambda *s: torch.randn(*s, dtype=torch.bfloat16) * 0.05)(B, S, D)),
            "w_gate": _w((lambda *s: torch.randn(*s, dtype=torch.bfloat16) * 0.05)(D, F)),
            "w_up": _w((lambda *s: torch.randn(*s, dtype=torch.bfloat16) * 0.05)(D, F)),
            "w_down": _w((lambda *s: torch.randn(*s, dtype=torch.bfloat16) * 0.05)(F, D)),
        }
    _B_in = _B_setup()

    return {
        "A_u": _A_in["u"],
        "A_log_A_real": _A_in["log_A_real"],
        "A_A_imag": _A_in["A_imag"],
        "A_C_real": _A_in["C_real"],
        "A_C_imag": _A_in["C_imag"],
        "A_log_dt": _A_in["log_dt"],
        "A_D_skip": _A_in["D_skip"],
        "B_x": _B_in["x"],
        "B_w_gate": _B_in["w_gate"],
        "B_w_up": _B_in["w_up"],
        "B_w_down": _B_in["w_down"],
    }

def reference(A_u, A_log_A_real, A_A_imag, A_C_real, A_C_imag, A_log_dt, A_D_skip, B_x, B_w_gate, B_w_up, B_w_down):
    def _A_ref(u, log_A_real, A_imag, C_real, C_imag, log_dt, D_skip):
        L = u.shape[1]
        dt = torch.exp(log_dt)
        A = -torch.exp(log_A_real) + 1j * A_imag
        C = (C_real + 1j * C_imag) * dt[:, None]
        pos = (lambda x, dt: x.to(dt))(torch.arange(L), log_dt.dtype)
        P = torch.exp((A * dt[:, None])[:, :, None] * pos[None, None, :])
        K = 2.0 * torch.einsum("dn,dnl->dl", C, P).real
        L2 = 2 * L
        u_t = (lambda x, *d: x.permute(*d))(u, 0, 2, 1)
        Kf = (lambda x, *a, **k: torch.fft.rfft(x.float(), *a, **k))(K, L2)
        Uf = (lambda x, *a, **k: torch.fft.rfft(x.float(), *a, **k))(u_t, L2)
        y = (lambda x, *a, **k: torch.fft.irfft(x, *a, **k).to(torch.bfloat16))(Uf * Kf[None, :, :], L2)[:, :, :L]
        y = (lambda x, *d: x.permute(*d))(y, 0, 2, 1)
        return y + u * D_skip[None, None, :]

    def _B_ref(x, w_gate, w_up, w_down):
        g = torch.einsum("bsd,df->bsf", x, w_gate)
        u = torch.einsum("bsd,df->bsf", x, w_up)
        h = _sigmoid(g) * u
        return torch.einsum("bsf,fd->bsd", h, w_down)

    x = A_u
    x = x + _A_ref(_layernorm(x, axis=-1), A_log_A_real, A_A_imag, A_C_real, A_C_imag, A_log_dt, A_D_skip)
    x = x + _B_ref(_layernorm(x, axis=-1), B_w_gate, B_w_up, B_w_down)
    x = x + _A_ref(_layernorm(x, axis=-1), A_log_A_real, A_A_imag, A_C_real, A_C_imag, A_log_dt, A_D_skip)
    x = x + _B_ref(_layernorm(x, axis=-1), B_w_gate, B_w_up, B_w_down)
    return x
```

```cpp
#include <cuda_runtime.h>
#include <cuda_bf16.h>
#include <cuda_fp16.h>
#include <cuda.h>
#include <stdint.h>

namespace {

typedef __nv_bfloat16 bf16;

constexpr int SEQ = 2048;
constexpr int DM = 512;
constexpr int NMODE = 128;
constexpr int FF = 1376;
constexpr int NCTA = 128;
constexpr int NTHR = 384;
constexpr int CSP = 1408;
constexpr int PAW = 1152;
constexpr int PTW = 1408;
constexpr int SPIN_LIMIT = 1 << 20;

constexpr uint32_t SM_X = 0;
constexpr uint32_t SM_WR = 131072;
constexpr uint32_t SM_MISC = 212992;
constexpr uint32_t SM_SMALL = 229376;
constexpr uint32_t SM_TOTAL = 232448;
constexpr uint32_t SM_CONV = 65536;
constexpr uint32_t CV_U = SM_CONV;
constexpr uint32_t CV_B97 = SM_CONV + 20480;
constexpr uint32_t CV_E0 = SM_CONV + 36864;
constexpr uint32_t CV_XS = SM_CONV + 49152;
constexpr uint32_t CV_E1 = SM_MISC;
constexpr uint32_t KG_A = 0;
constexpr uint32_t KG_B = 12288;
constexpr uint32_t SM_STRIP = SM_WR + 16384;
constexpr uint32_t SM_PT = SM_WR + 3 * 16384;
constexpr uint32_t SM_STAT = SM_MISC;
constexpr uint32_t SM_RES = 98304;
constexpr uint32_t SM_G2S = 114688;
constexpr uint32_t G2_STAGE = 49152;
constexpr uint32_t SM_BAR = SM_SMALL;
constexpr uint32_t SM_CS = SM_SMALL + 512;
constexpr uint32_t SM_ST = SM_SMALL + 1920;

enum {
  B_WFULL = 0, B_WEMPTY = 6, B_XFULL = 12, B_CSFULL = 20, B_G2FULL = 21, B_G2EMPTY = 25, B_RESFULL = 29,
  B_PTFULL = 30, B_XSFULL = 31, B_CONVDONE = 32, B_G1DONE = 33, B_G2DONE = 34, B_TAILDONE = 35, B_STFULL = 36, B_PUB = 37, B_KGDONE = 39, B_STAGED = 40, B_STRIP = 41, B_STRIPDONE = 42, B_PTDONE = 43, B_PTSAVED = 44
};
enum { F_0 = 0, F_CS = 1, F_3 = 2, F_S = 4, F_1 = 8, F_2 = 32, F_COUNT = 224 };

__device__ __align__(1024) bf16 g_xT[3][DM * SEQ];
__device__ __align__(1024) bf16 g_h[32 * 24 * 4096];
__device__ __align__(128) uint32_t g_ptab[DM * PTW];
__device__ __align__(128) float2 g_stat1[SEQ];
__device__ __align__(128) float2 g_stat3[SEQ];
__device__ __align__(128) float2 g_stat2[2][4][SEQ];
__device__ __align__(128) float g_cs[2 * CSP];
__device__ __align__(128) unsigned g_flag[F_COUNT * 8];
__device__ unsigned g_epoch;

#define TS(k)
#define TSA(k)
#define TR(k)
#define TRA(k)
#define TRS(k)

struct Params {
  const bf16 *x0, *logA, *Aim, *Cre, *Cim, *logdt, *Dsk, *wg, *wu, *wd;
  bf16* out;
};

__device__ __forceinline__ uint32_t smem_u32(const void* p) { return (uint32_t)__cvta_generic_to_shared(p); }
__device__ __forceinline__ void mbar_init(uint32_t a, uint32_t c) { asm volatile("mbarrier.init.shared::cta.b64 [%0], %1;" ::"r"(a), "r"(c) : "memory"); }
__device__ __forceinline__ void mbar_expect(uint32_t a, uint32_t b) { asm volatile("mbarrier.arrive.expect_tx.shared::cta.b64 _, [%0], %1;" ::"r"(a), "r"(b) : "memory"); }
__device__ __forceinline__ void mbar_arrive(uint32_t a) { asm volatile("mbarrier.arrive.shared::cta.b64 _, [%0];" ::"r"(a) : "memory"); }
__device__ __forceinline__ void mbar_wait(uint32_t a, uint32_t par) {
  asm volatile("{\n.reg .pred p;\n.reg .u32 n;\nmov.u32 n, 0;\n"
               "LW:\nmbarrier.try_wait.parity.shared::cta.b64 p, [%0], %1;\n@p bra LD;\n"
               "add.u32 n, n, 1;\nsetp.lt.u32 p, n, %2;\n@p bra LW;\ntrap;\nLD:\n}\n" ::"r"(a), "r"(par), "n"(SPIN_LIMIT) : "memory");
}
__device__ __forceinline__ void mbar_wait_fast(uint32_t a, uint32_t par) {
  asm volatile("{\n.reg .pred p;\nLW:\nmbarrier.try_wait.parity.shared::cta.b64 p, [%0], %1;\n@!p bra LW;\n}\n" ::"r"(a), "r"(par) : "memory");
}
__device__ __forceinline__ void flag_wait(const unsigned* f, unsigned target) {
  asm volatile("{\n.reg .pred p;\n.reg .u32 n, v;\nmov.u32 n, 0;\n"
               "LW:\nld.acquire.gpu.global.u32 v, [%0];\nsub.u32 v, v, %1;\nsetp.ge.s32 p, v, 0;\n@p bra LD;\n"
               "add.u32 n, n, 1;\nsetp.lt.u32 p, n, %2;\n@p bra LW;\ntrap;\nLD:\n}\n" ::"l"(f), "r"(target), "n"(SPIN_LIMIT) : "memory");
}
__device__ __forceinline__ bool elect_one() {
  uint32_t r;
  asm volatile("{\n.reg .pred p;\nelect.sync _|p, 0xffffffff;\nselp.u32 %0, 1, 0, p;\n}\n" : "=r"(r));
  return r != 0;
}
__device__ __forceinline__ void flag_publish(unsigned* f) {
  asm volatile("fence.acq_rel.gpu;" ::: "memory");
  asm volatile("red.relaxed.gpu.global.add.u32 [%0], 1;" ::"l"(f) : "memory");
}
__device__ __forceinline__ void bar_sync(int id, int n) { asm volatile("bar.sync %0, %1;" ::"r"(id), "r"(n) : "memory"); }
__device__ __forceinline__ void bar_arrive(int id, int n) { asm volatile("bar.arrive %0, %1;" ::"r"(id), "r"(n) : "memory"); }
__device__ __forceinline__ void fence_async_smem() { asm volatile("fence.proxy.async.shared::cta;" ::: "memory"); }
__device__ __forceinline__ void fence_async_all() { asm volatile("fence.proxy.async.global;" ::: "memory"); }
__device__ __forceinline__ void wg_fence() { asm volatile("wgmma.fence.sync.aligned;" ::: "memory"); }
__device__ __forceinline__ void wg_commit() { asm volatile("wgmma.commit_group.sync.aligned;" ::: "memory"); }
template <int N> __device__ __forceinline__ void wg_wait() { asm volatile("wgmma.wait_group.sync.aligned %0;" ::"n"(N) : "memory"); }

__device__ __forceinline__ void bulk_g2s(uint32_t dst, const void* src, uint32_t bytes, uint32_t bar) {
  asm volatile("cp.async.bulk.shared::cluster.global.mbarrier::complete_tx::bytes [%0], [%1], %2, [%3];" ::"r"(dst), "l"(src), "r"(bytes), "r"(bar) : "memory");
}
__device__ __forceinline__ void tma_2d(uint32_t dst, const CUtensorMap* m, int c0, int c1, uint32_t bar) {
  asm volatile("cp.async.bulk.tensor.2d.shared::cluster.global.mbarrier::complete_tx::bytes [%0], [%1, {%2, %3}], [%4];"
               ::"r"(dst), "l"(m), "r"(c0), "r"(c1), "r"(bar) : "memory");
}
__device__ __forceinline__ void tma_4d(uint32_t dst, const CUtensorMap* m, int c0, int c1, int c2, int c3, uint32_t bar) {
  asm volatile("cp.async.bulk.tensor.4d.shared::cluster.global.mbarrier::complete_tx::bytes [%0], [%1, {%2, %3, %4, %5}], [%6];"
               ::"r"(dst), "l"(m), "r"(c0), "r"(c1), "r"(c2), "r"(c3), "r"(bar) : "memory");
}
__device__ __forceinline__ void tma_3d(uint32_t dst, const CUtensorMap* m, int c0, int c1, int c2, uint32_t bar) {
  asm volatile("cp.async.bulk.tensor.3d.shared::cluster.global.mbarrier::complete_tx::bytes [%0], [%1, {%2, %3, %4}], [%5];"
               ::"r"(dst), "l"(m), "r"(c0), "r"(c1), "r"(c2), "r"(bar) : "memory");
}
__device__ __forceinline__ void tma_5d(uint32_t dst, const CUtensorMap* m, int c0, int c1, int c2, int c3, int c4, uint32_t bar) {
  asm volatile("cp.async.bulk.tensor.5d.shared::cluster.global.mbarrier::complete_tx::bytes [%0], [%1, {%2, %3, %4, %5, %6}], [%7];"
               ::"r"(dst), "l"(m), "r"(c0), "r"(c1), "r"(c2), "r"(c3), "r"(c4), "r"(bar) : "memory");
}
__device__ __forceinline__ void tmap_prefetch(const CUtensorMap* m) { asm volatile("prefetch.tensormap [%0];" ::"l"(m) : "memory"); }
__device__ __forceinline__ void l2_prefetch(const void* p, uint32_t bytes) { asm volatile("cp.async.bulk.prefetch.L2.global [%0], %1;" ::"l"(p), "r"(bytes) : "memory"); }

template <class T> __device__ __forceinline__ T* sptr(uint32_t a) { return reinterpret_cast<T*>(__cvta_shared_to_generic(a)); }
__device__ __forceinline__ uint32_t lds32(uint32_t a) { return *sptr<const uint32_t>(a); }
__device__ __forceinline__ float ldsf(uint32_t a) { return *sptr<const float>(a); }
__device__ __forceinline__ float2 ldsf2(uint32_t a) { return *sptr<const float2>(a); }
__device__ __forceinline__ uint4 lds128(uint32_t a) { return *sptr<const uint4>(a); }
__device__ __forceinline__ void sts32(uint32_t a, uint32_t v) { *sptr<uint32_t>(a) = v; }
__device__ __forceinline__ void stsf(uint32_t a, float v) { *sptr<float>(a) = v; }
__device__ __forceinline__ void stsf2(uint32_t a, float x, float y) { *sptr<float2>(a) = make_float2(x, y); }
__device__ __forceinline__ void sts128(uint32_t a, uint4 v) { *sptr<uint4>(a) = v; }
__device__ __forceinline__ void ldsm4t(uint32_t a, uint32_t& r0, uint32_t& r1, uint32_t& r2, uint32_t& r3) {
  asm volatile("ldmatrix.sync.aligned.m8n8.x4.trans.shared.b16 {%0, %1, %2, %3}, [%4];" : "=r"(r0), "=r"(r1), "=r"(r2), "=r"(r3) : "r"(a) : "memory");
}
__device__ __forceinline__ void red_add4(float* p, uint4 v) {
  asm volatile("red.relaxed.gpu.global.add.v4.f32 [%0], {%1, %2, %3, %4};" ::"l"(p), "f"(__uint_as_float(v.x)), "f"(__uint_as_float(v.y)),
               "f"(__uint_as_float(v.z)), "f"(__uint_as_float(v.w)) : "memory");
}
__device__ __forceinline__ void ldsm4(uint32_t a, uint32_t& r0, uint32_t& r1, uint32_t& r2, uint32_t& r3) {
  asm volatile("ldmatrix.sync.aligned.m8n8.x4.shared.b16 {%0, %1, %2, %3}, [%4];" : "=r"(r0), "=r"(r1), "=r"(r2), "=r"(r3) : "r"(a) : "memory");
}
__device__ __forceinline__ void stsm4(uint32_t a, uint32_t r0, uint32_t r1, uint32_t r2, uint32_t r3) {
  asm volatile("stmatrix.sync.aligned.m8n8.x4.shared.b16 [%0], {%1, %2, %3, %4};" ::"r"(a), "r"(r0), "r"(r1), "r"(r2), "r"(r3) : "memory");
}
__device__ __forceinline__ void stsm4t(uint32_t a, uint32_t r0, uint32_t r1, uint32_t r2, uint32_t r3) {
  asm volatile("stmatrix.sync.aligned.m8n8.x4.trans.shared.b16 [%0], {%1, %2, %3, %4};" ::"r"(a), "r"(r0), "r"(r1), "r"(r2), "r"(r3) : "memory");
}
__device__ __forceinline__ uint4 ldg128_cg(const void* p) { uint4 v; asm volatile("ld.global.cg.v4.b32 {%0, %1, %2, %3}, [%4];" : "=r"(v.x), "=r"(v.y), "=r"(v.z), "=r"(v.w) : "l"(p) : "memory"); return v; }
__device__ __forceinline__ uint4 ldg128_nc(const void* p) { uint4 v; asm volatile("ld.global.nc.v4.b32 {%0, %1, %2, %3}, [%4];" : "=r"(v.x), "=r"(v.y), "=r"(v.z), "=r"(v.w) : "l"(p)); return v; }

__device__ __forceinline__ float bf_lo(uint32_t v) { return __uint_as_float(v << 16); }
__device__ __forceinline__ float bf_hi(uint32_t v) { return __uint_as_float(v & 0xffff0000u); }
__device__ __forceinline__ uint32_t pack_bf(float lo, float hi) { uint32_t r; asm("cvt.rn.bf16x2.f32 %0, %1, %2;" : "=r"(r) : "f"(hi), "f"(lo)); return r; }
__device__ __forceinline__ uint32_t pack_h(float lo, float hi) { uint32_t r; asm("cvt.rn.f16x2.f32 %0, %1, %2;" : "=r"(r) : "f"(hi), "f"(lo)); return r; }
__device__ __forceinline__ uint32_t bf2_add(uint32_t a, uint32_t b) { uint32_t r; asm("add.rn.bf16x2 %0, %1, %2;" : "=r"(r) : "r"(a), "r"(b)); return r; }
__device__ __forceinline__ uint32_t bf2_sub(uint32_t a, uint32_t b) { uint32_t r; asm("sub.rn.bf16x2 %0, %1, %2;" : "=r"(r) : "r"(a), "r"(b)); return r; }
__device__ __forceinline__ float bf_round(float x) { return bf_lo(pack_bf(x, 0.f)); }
__device__ __forceinline__ float2 unpack_h(uint32_t v) { return __half22float2(*reinterpret_cast<const __half2*>(&v)); }
__device__ __forceinline__ float ex2f(float x) { float y; asm("ex2.approx.ftz.f32 %0, %1;" : "=f"(y) : "f"(x)); return y; }
__device__ __forceinline__ float rcpf(float x) { float y; asm("rcp.approx.ftz.f32 %0, %1;" : "=f"(y) : "f"(x)); return y; }
__device__ __forceinline__ float bf2f(bf16 v) { return __bfloat162float(v); }

template <int N> __device__ __forceinline__ void pin_regs(float (&a)[N]) {
#pragma unroll
  for (int i = 0; i < N; i++) asm volatile("" : "+f"(a[i])::"memory");
}

__device__ __forceinline__ uint32_t g2_stage_off(uint32_t st) { return st < 2 ? SM_WR + st * G2_STAGE : (st - 2) * G2_STAGE; }
__device__ __forceinline__ uint32_t desc_lo(uint32_t addr, uint32_t lbo) { return ((addr & 0x3FFFF) >> 4) | ((lbo >> 4) << 16); }

__device__ __forceinline__ float2 ln_finalize(float sum, float sq) {
  const float mean = sum * (1.0f / DM);
  const float var = fmaxf(fmaf(-mean, mean, sq * (1.0f / DM)), 0.f);
  const float ve = bf_round(bf_round(var) + 1e-5f);
  float s;
  asm("sqrt.approx.ftz.f32 %0, %1;" : "=f"(s) : "f"(ve));
  return make_float2(bf_round(mean), rcpf(bf_round(s)));
}

__device__ __forceinline__ void wg_g1_n128(float (&d)[64], uint32_t da, uint32_t db, int scale_d) {
  asm volatile("{\n.reg .pred p;\n.reg .b64 da, db;\n.reg .b32 ha, hb;\nsetp.ne.b32 p, %66, 0;\n"
    "mov.b32 ha, 1073741888;\nmov.b32 hb, 1073741888;\nmov.b64 da, {%64, ha};\nmov.b64 db, {%65, hb};\n"
    "wgmma.mma_async.sync.aligned.m64n128k16.f32.bf16.bf16 "
    "{%0, %1, %2, %3, %4, %5, %6, %7, %8, %9, %10, %11, %12, %13, %14, %15, %16, %17, %18, %19, %20, %21, %22, %23, %24, %25, %26, %27, %28, %29, %30, %31, %32, %33, %34, %35, %36, %37, %38, %39, %40, %41, %42, %43, %44, %45, %46, %47, %48, %49, %50, %51, %52, %53, %54, %55, %56, %57, %58, %59, %60, %61, %62, %63}, "
    "da, db, p, 1, 1, 1, 1;\n}\n"
    : "+f"(d[0]), "+f"(d[1]), "+f"(d[2]), "+f"(d[3]), "+f"(d[4]), "+f"(d[5]), "+f"(d[6]), "+f"(d[7]), "+f"(d[8]), "+f"(d[9]), "+f"(d[10]), "+f"(d[11]), "+f"(d[12]), "+f"(d[13]), "+f"(d[14]), "+f"(d[15]), "+f"(d[16]), "+f"(d[17]), "+f"(d[18]), "+f"(d[19]), "+f"(d[20]), "+f"(d[21]), "+f"(d[22]), "+f"(d[23]), "+f"(d[24]), "+f"(d[25]), "+f"(d[26]), "+f"(d[27]), "+f"(d[28]), "+f"(d[29]), "+f"(d[30]), "+f"(d[31]), "+f"(d[32]), "+f"(d[33]), "+f"(d[34]), "+f"(d[35]), "+f"(d[36]), "+f"(d[37]), "+f"(d[38]), "+f"(d[39]), "+f"(d[40]), "+f"(d[41]), "+f"(d[42]), "+f"(d[43]), "+f"(d[44]), "+f"(d[45]), "+f"(d[46]), "+f"(d[47]), "+f"(d[48]), "+f"(d[49]), "+f"(d[50]), "+f"(d[51]), "+f"(d[52]), "+f"(d[53]), "+f"(d[54]), "+f"(d[55]), "+f"(d[56]), "+f"(d[57]), "+f"(d[58]), "+f"(d[59]), "+f"(d[60]), "+f"(d[61]), "+f"(d[62]), "+f"(d[63])
    : "r"(da), "r"(db), "r"(scale_d));
}
__device__ __forceinline__ void wg_g1_n112(float (&d)[64], uint32_t da, uint32_t db, int scale_d) {
  asm volatile("{\n.reg .pred p;\n.reg .b64 da, db;\n.reg .b32 ha, hb;\nsetp.ne.b32 p, %58, 0;\n"
    "mov.b32 ha, 1073741888;\nmov.b32 hb, 1073741888;\nmov.b64 da, {%56, ha};\nmov.b64 db, {%57, hb};\n"
    "wgmma.mma_async.sync.aligned.m64n112k16.f32.bf16.bf16 "
    "{%0, %1, %2, %3, %4, %5, %6, %7, %8, %9, %10, %11, %12, %13, %14, %15, %16, %17, %18, %19, %20, %21, %22, %23, %24, %25, %26, %27, %28, %29, %30, %31, %32, %33, %34, %35, %36, %37, %38, %39, %40, %41, %42, %43, %44, %45, %46, %47, %48, %49, %50, %51, %52, %53, %54, %55}, "
    "da, db, p, 1, 1, 1, 1;\n}\n"
    : "+f"(d[0]), "+f"(d[1]), "+f"(d[2]), "+f"(d[3]), "+f"(d[4]), "+f"(d[5]), "+f"(d[6]), "+f"(d[7]), "+f"(d[8]), "+f"(d[9]), "+f"(d[10]), "+f"(d[11]), "+f"(d[12]), "+f"(d[13]), "+f"(d[14]), "+f"(d[15]), "+f"(d[16]), "+f"(d[17]), "+f"(d[18]), "+f"(d[19]), "+f"(d[20]), "+f"(d[21]), "+f"(d[22]), "+f"(d[23]), "+f"(d[24]), "+f"(d[25]), "+f"(d[26]), "+f"(d[27]), "+f"(d[28]), "+f"(d[29]), "+f"(d[30]), "+f"(d[31]), "+f"(d[32]), "+f"(d[33]), "+f"(d[34]), "+f"(d[35]), "+f"(d[36]), "+f"(d[37]), "+f"(d[38]), "+f"(d[39]), "+f"(d[40]), "+f"(d[41]), "+f"(d[42]), "+f"(d[43]), "+f"(d[44]), "+f"(d[45]), "+f"(d[46]), "+f"(d[47]), "+f"(d[48]), "+f"(d[49]), "+f"(d[50]), "+f"(d[51]), "+f"(d[52]), "+f"(d[53]), "+f"(d[54]), "+f"(d[55])
    : "r"(da), "r"(db), "r"(scale_d));
}
__device__ __forceinline__ void wg_g2_n64(float (&d)[32], uint32_t da, uint32_t db, int scale_d) {
  asm volatile("{\n.reg .pred p;\n.reg .b64 da, db;\n.reg .b32 ha, hb;\nsetp.ne.b32 p, %34, 0;\n"
    "mov.b32 ha, 1073741888;\nmov.b32 hb, 8;\nmov.b64 da, {%32, ha};\nmov.b64 db, {%33, hb};\n"
    "wgmma.mma_async.sync.aligned.m64n64k16.f32.bf16.bf16 "
    "{%0, %1, %2, %3, %4, %5, %6, %7, %8, %9, %10, %11, %12, %13, %14, %15, %16, %17, %18, %19, %20, %21, %22, %23, %24, %25, %26, %27, %28, %29, %30, %31}, "
    "da, db, p, 1, 1, 1, 0;\n}\n"
    : "+f"(d[0]), "+f"(d[1]), "+f"(d[2]), "+f"(d[3]), "+f"(d[4]), "+f"(d[5]), "+f"(d[6]), "+f"(d[7]), "+f"(d[8]), "+f"(d[9]), "+f"(d[10]), "+f"(d[11]), "+f"(d[12]), "+f"(d[13]), "+f"(d[14]), "+f"(d[15]), "+f"(d[16]), "+f"(d[17]), "+f"(d[18]), "+f"(d[19]), "+f"(d[20]), "+f"(d[21]), "+f"(d[22]), "+f"(d[23]), "+f"(d[24]), "+f"(d[25]), "+f"(d[26]), "+f"(d[27]), "+f"(d[28]), "+f"(d[29]), "+f"(d[30]), "+f"(d[31])
    : "r"(da), "r"(db), "r"(scale_d));
}
__device__ __forceinline__ void wg_kg_n32(float (&d)[16], uint32_t da, uint32_t db, int scale_d) {
  asm volatile("{\n.reg .pred p;\n.reg .b64 da, db;\n.reg .b32 ha, hb;\nsetp.ne.b32 p, %18, 0;\n"
    "mov.b32 ha, 1073741888;\nmov.b32 hb, 1073741888;\nmov.b64 da, {%16, ha};\nmov.b64 db, {%17, hb};\n"
    "wgmma.mma_async.sync.aligned.m64n32k16.f32.f16.f16 "
    "{%0, %1, %2, %3, %4, %5, %6, %7, %8, %9, %10, %11, %12, %13, %14, %15}, "
    "da, db, p, 1, 1, 0, 0;\n}\n"
    : "+f"(d[0]), "+f"(d[1]), "+f"(d[2]), "+f"(d[3]), "+f"(d[4]), "+f"(d[5]), "+f"(d[6]), "+f"(d[7]), "+f"(d[8]), "+f"(d[9]), "+f"(d[10]), "+f"(d[11]), "+f"(d[12]), "+f"(d[13]), "+f"(d[14]), "+f"(d[15])
    : "r"(da), "r"(db), "r"(scale_d));
}
__device__ __forceinline__ void wg_cv_n64(float (&d)[32], uint32_t a0, uint32_t a1, uint32_t a2, uint32_t a3, uint32_t db, int scale_d) {
  asm volatile("{\n.reg .pred p;\n.reg .b64 db;\n.reg .b32 hb;\nsetp.ne.b32 p, %37, 0;\n"
    "mov.b32 hb, 2147483680;\nmov.b64 db, {%36, hb};\n"
    "wgmma.mma_async.sync.aligned.m64n64k16.f32.f16.f16 "
    "{%0, %1, %2, %3, %4, %5, %6, %7, %8, %9, %10, %11, %12, %13, %14, %15, %16, %17, %18, %19, %20, %21, %22, %23, %24, %25, %26, %27, %28, %29, %30, %31}, "
    "{%32, %33, %34, %35}, db, p, 1, 1, 0;\n}\n"
    : "+f"(d[0]), "+f"(d[1]), "+f"(d[2]), "+f"(d[3]), "+f"(d[4]), "+f"(d[5]), "+f"(d[6]), "+f"(d[7]), "+f"(d[8]), "+f"(d[9]), "+f"(d[10]), "+f"(d[11]), "+f"(d[12]), "+f"(d[13]), "+f"(d[14]), "+f"(d[15]), "+f"(d[16]), "+f"(d[17]), "+f"(d[18]), "+f"(d[19]), "+f"(d[20]), "+f"(d[21]), "+f"(d[22]), "+f"(d[23]), "+f"(d[24]), "+f"(d[25]), "+f"(d[26]), "+f"(d[27]), "+f"(d[28]), "+f"(d[29]), "+f"(d[30]), "+f"(d[31])
    : "r"(a0), "r"(a1), "r"(a2), "r"(a3), "r"(db), "r"(scale_d));
}
__device__ __forceinline__ void wg_cv_n56(float (&d)[28], uint32_t a0, uint32_t a1, uint32_t a2, uint32_t a3, uint32_t db, int scale_d) {
  asm volatile("{\n.reg .pred p;\n.reg .b64 db;\n.reg .b32 hb;\nsetp.ne.b32 p, %33, 0;\n"
    "mov.b32 hb, 2147483680;\nmov.b64 db, {%32, hb};\n"
    "wgmma.mma_async.sync.aligned.m64n56k16.f32.f16.f16 "
    "{%0, %1, %2, %3, %4, %5, %6, %7, %8, %9, %10, %11, %12, %13, %14, %15, %16, %17, %18, %19, %20, %21, %22, %23, %24, %25, %26, %27}, "
    "{%28, %29, %30, %31}, db, p, 1, 1, 0;\n}\n"
    : "+f"(d[0]), "+f"(d[1]), "+f"(d[2]), "+f"(d[3]), "+f"(d[4]), "+f"(d[5]), "+f"(d[6]), "+f"(d[7]), "+f"(d[8]), "+f"(d[9]), "+f"(d[10]), "+f"(d[11]), "+f"(d[12]), "+f"(d[13]), "+f"(d[14]), "+f"(d[15]), "+f"(d[16]), "+f"(d[17]), "+f"(d[18]), "+f"(d[19]), "+f"(d[20]), "+f"(d[21]), "+f"(d[22]), "+f"(d[23]), "+f"(d[24]), "+f"(d[25]), "+f"(d[26]), "+f"(d[27])
    : "r"(a0), "r"(a1), "r"(a2), "r"(a3), "r"(db), "r"(scale_d));
}
__device__ __forceinline__ void wg_cv_n40(float (&d)[20], uint32_t a0, uint32_t a1, uint32_t a2, uint32_t a3, uint32_t db, int scale_d) {
  asm volatile("{\n.reg .pred p;\n.reg .b64 db;\n.reg .b32 hb;\nsetp.ne.b32 p, %25, 0;\n"
    "mov.b32 hb, 2147483680;\nmov.b64 db, {%24, hb};\n"
    "wgmma.mma_async.sync.aligned.m64n40k16.f32.f16.f16 "
    "{%0, %1, %2, %3, %4, %5, %6, %7, %8, %9, %10, %11, %12, %13, %14, %15, %16, %17, %18, %19}, "
    "{%20, %21, %22, %23}, db, p, 1, 1, 0;\n}\n"
    : "+f"(d[0]), "+f"(d[1]), "+f"(d[2]), "+f"(d[3]), "+f"(d[4]), "+f"(d[5]), "+f"(d[6]), "+f"(d[7]), "+f"(d[8]), "+f"(d[9]), "+f"(d[10]), "+f"(d[11]), "+f"(d[12]), "+f"(d[13]), "+f"(d[14]), "+f"(d[15]), "+f"(d[16]), "+f"(d[17]), "+f"(d[18]), "+f"(d[19])
    : "r"(a0), "r"(a1), "r"(a2), "r"(a3), "r"(db), "r"(scale_d));
}
__device__ __forceinline__ void wg_cv_n16t(float (&d)[8], uint32_t a0, uint32_t a1, uint32_t a2, uint32_t a3, uint32_t db, int scale_d) {
  asm volatile("{\n.reg .pred p;\n.reg .b64 db;\n.reg .b32 hb;\nsetp.ne.b32 p, %13, 0;\n"
    "mov.b32 hb, 3221225488;\nmov.b64 db, {%12, hb};\n"
    "wgmma.mma_async.sync.aligned.m64n16k16.f32.f16.f16 "
    "{%0, %1, %2, %3, %4, %5, %6, %7}, "
    "{%8, %9, %10, %11}, db, p, 1, 1, 1;\n}\n"
    : "+f"(d[0]), "+f"(d[1]), "+f"(d[2]), "+f"(d[3]), "+f"(d[4]), "+f"(d[5]), "+f"(d[6]), "+f"(d[7])
    : "r"(a0), "r"(a1), "r"(a2), "r"(a3), "r"(db), "r"(scale_d));
}

__device__ __forceinline__ float2 cmul(float2 a, float2 b) {
  return make_float2(fmaf(a.x, b.x, -a.y * b.y), fmaf(a.x, b.y, a.y * b.x));
}
__device__ __forceinline__ float2 cexp_p(float ar, float ai, float p) {
  float xr = ar * p, xi = ai * p;
  float mag = ex2f(xr * 1.4426950408889634f);
  float k = rintf(xi * 0.15915494309189535f);
  float r = fmaf(-k, 6.2831854820251465f, xi);
  r = fmaf(-k, -1.7484555314695172e-07f, r);
  float s, c;
  __sincosf(r, &s, &c);
  return make_float2(mag * c, mag * s);
}
__device__ __forceinline__ int pos_index(int j) {
  int b = (int)(pack_bf((float)j, 0.f) & 0xffffu) - 17024;
  return j < 128 ? j : b;
}

struct KParam { float logA, aim, cre, cim, logdt; };

__device__ __forceinline__ void kgen(uint32_t sb, int w, int wp, int lane, const KParam (&kp)[2], float (&kinv)[2]) {
  const int t = wp * 32 + lane;
  float ar[2], ai[2];
  float2 C[2];
  const uint32_t mxa = sb + SM_MISC + 12288 + w * 32;
#pragma unroll
  for (int v = 0; v < 2; v++) {
    const float dt = bf_round(expf(kp[v].logdt));
    const float lar = -bf_round(expf(kp[v].logA));
    ar[v] = lar * dt; ai[v] = kp[v].aim * dt;
    C[v] = make_float2(kp[v].cre * dt, kp[v].cim * dt);
    float mx = fmaxf(fabsf(C[v].x), fabsf(C[v].y));
#pragma unroll
    for (int o = 16; o; o >>= 1) mx = fmaxf(mx, __shfl_xor_sync(0xffffffffu, mx, o));
    if (lane == 0) stsf(mxa + v * 16 + wp * 4, mx);
  }
  bar_sync(1 + w, 128);
#pragma unroll
  for (int v = 0; v < 2; v++) {
    const uint4 m4 = lds128(mxa + v * 16);
    const float mx = fmaxf(fmaxf(__uint_as_float(m4.x), __uint_as_float(m4.y)), fmaxf(__uint_as_float(m4.z), __uint_as_float(m4.w)));
    int e = (__float_as_uint(mx) >> 23) & 255;
    e = min(max(e, 4), 254);
    const float scale2 = __uint_as_float((uint32_t)(258 - e) << 23);
    kinv[v] = __uint_as_float((uint32_t)(e - 3) << 23);
    C[v].x *= scale2; C[v].y *= scale2;
  }
  const uint32_t ga = sb + KG_A + w * 28672 + wp * 3072 + lane * 4;
  const uint32_t fa = sb + KG_B + w * 28672 + wp * 4096 + lane * 4;
  auto putG = [&](int v, int h, float2 g) { sts32(((ga + v * 57344) ^ ((h & 7) << 4)) + h * 128, pack_h(g.x, -g.y)); };
  float2 E8[2];
#pragma unroll
  for (int v = 0; v < 2; v++) {
    const float2 E1 = cexp_p(ar[v], ai[v], 1.f), E256 = cexp_p(ar[v], ai[v], 256.f);
    const float2 E2 = cmul(E1, E1), E4 = cmul(E2, E2), E512 = cmul(E256, E256), E1024 = cmul(E512, E512);
    E8[v] = cmul(E4, E4);
    {
      float2 g0 = C[v], g1 = cmul(C[v], E1);
      putG(v, 0, g0); putG(v, 1, g1);
#pragma unroll
      for (int h = 2; h < 8; h += 2) { g0 = cmul(g0, E2); g1 = cmul(g1, E2); putG(v, h, g0); putG(v, h + 1, g1); }
    }
    {
      const float2 g = cmul(C[v], E256), g4 = cmul(g, E4);
      putG(v, 8, g); putG(v, 9, cmul(g, E2)); putG(v, 10, g4); putG(v, 11, cmul(g4, E2));
    }
    {
      const float2 g = cmul(C[v], E512), g2 = cmul(g, E256);
      putG(v, 12, g); putG(v, 13, cmul(g, E4)); putG(v, 14, g2); putG(v, 15, cmul(g2, E4));
    }
    {
      const float2 g = cmul(C[v], E1024), g2 = cmul(g, E512);
      putG(v, 16, g); putG(v, 17, cmul(g, E256)); putG(v, 18, g2); putG(v, 19, cmul(g2, E256)); putG(v, 20, cmul(g, E1024));
    }
  }
  {
    float2 f[2][2], E16[2];
#pragma unroll
    for (int v = 0; v < 2; v++) { E16[v] = cmul(E8[v], E8[v]); f[v][0] = make_float2(1.f, 0.f); f[v][1] = E8[v]; }
#pragma unroll 2
    for (int o = 0; o < 32; o += 2) {
      const uint32_t a0 = (fa ^ ((o & 7) << 4)) + o * 128, a1 = (fa ^ (((o + 1) & 7) << 4)) + (o + 1) * 128;
#pragma unroll
      for (int v = 0; v < 2; v++) {
        sts32(a0 + v * 57344, pack_h(f[v][0].x, f[v][0].y));
        sts32(a1 + v * 57344, pack_h(f[v][1].x, f[v][1].y));
        f[v][0] = cmul(f[v][0], E16[v]); f[v][1] = cmul(f[v][1], E16[v]);
      }
    }
  }
  TS(37);
  fence_async_smem();
  bar_sync(1 + w, 128);
  float acc0[16], acc1[16];
#pragma unroll
  for (int i = 0; i < 16; i++) { acc0[i] = 0.f; acc1[i] = 0.f; }
  pin_regs(acc0); pin_regs(acc1);
  {
    const uint32_t da = desc_lo(sb + KG_A + w * 28672, 16), db = desc_lo(sb + KG_B + w * 28672, 16);
    wg_fence();
#pragma unroll 1
    for (int kb = 0; kb < 4; kb++) {
#pragma unroll
      for (int k = 0; k < 4; k++) {
        wg_kg_n32(acc0, da + kb * 192 + k * 2, db + kb * 256 + k * 2, (kb | k) != 0);
        wg_kg_n32(acc1, da + 3584 + kb * 192 + k * 2, db + 3584 + kb * 256 + k * 2, (kb | k) != 0);
      }
    }
    wg_commit();
    wg_wait<0>();
    pin_regs(acc0); pin_regs(acc1);
    if (lane == 0) mbar_arrive(sb + SM_BAR + 8 * B_KGDONE);
  }
  const uint32_t kt = sb + SM_MISC + w * 2592;
  {
    const int g = lane >> 2, c = lane & 3;
    if (wp == 0) {
      const int b2 = g < 4 ? 256 + g : 384 + 64 * ((g - 4) >> 1) + (g & 1), s2 = g < 4 ? 4 : 2;
      const uint32_t k0 = kt + (g + 16 * c) * 4, k1 = kt + (b2 + s2 * 2 * c) * 4;
#pragma unroll
      for (int nb = 0; nb < 4; nb++)
#pragma unroll
        for (int k = 0; k < 2; k++) {
          const int o = 8 * nb + k;
          stsf(k0 + 32 * o, acc0[4 * nb + k]); stsf(k0 + 32 * o + 5184, acc1[4 * nb + k]);
          stsf(k1 + s2 * 4 * o, acc0[4 * nb + 2 + k]); stsf(k1 + s2 * 4 * o + 5184, acc1[4 * nb + 2 + k]);
        }
    } else if (wp == 1) {
      if (g < 4) {
        const uint32_t k0 = kt + (512 + 32 * g + 2 * c) * 4;
#pragma unroll
        for (int nb = 0; nb < 4; nb++) { stsf2(k0 + 32 * nb, acc0[4 * nb], acc0[4 * nb + 1]); stsf2(k0 + 32 * nb + 5184, acc1[4 * nb], acc1[4 * nb + 1]); }
      } else if (g == 4 && c == 0) {
        stsf(kt + 640 * 4, acc0[0]); stsf(kt + 640 * 4 + 5184, acc1[0]);
      }
    }
  }
  bar_sync(1 + w, 128);
  TS(49);
  const uint32_t pt = sb + SM_PT + w * (PTW * 4);
#pragma unroll 1
  for (int i = 0; i < 3; i++) {
    const int q = t + 128 * i;
    if (q < PAW / 4) {
      const int x0 = 4 * q - 65;
      float kv[2][5];
#pragma unroll
      for (int k = 0; k < 5; k++) {
        const int x = x0 + k;
        const bool ok = x >= 0 && x <= 1028;
        const uint32_t a = kt + (ok ? pos_index(x) : 0) * 4;
#pragma unroll
        for (int v = 0; v < 2; v++) { const float f = ldsf(a + v * 5184); kv[v][k] = ok ? f : 0.f; }
      }
#pragma unroll
      for (int v = 0; v < 2; v++)
        sts128(pt + v * (2 * PTW * 4) + q * 16, make_uint4(pack_h(kv[v][1], kv[v][0]), pack_h(kv[v][2], kv[v][1]), pack_h(kv[v][3], kv[v][2]), pack_h(kv[v][4], kv[v][3])));
    }
  }
  {
    const int z = t - 64;
#pragma unroll
    for (int v = 0; v < 2; v++) {
      const uint32_t k0 = kt + v * 5184 + 8 * max(z, 0);
      const float a = ldsf(k0 + 511 * 4), b = ldsf(k0 + 512 * 4), c = ldsf(k0 + 513 * 4), d = ldsf(k0 + 514 * 4);
      sts32(pt + v * (2 * PTW * 4) + (PAW + t) * 4, pack_h(z >= 0 ? d : 0.f, z >= 1 ? b : 0.f));
      sts32(pt + v * (2 * PTW * 4) + (PAW + 128 + t) * 4, pack_h(z >= 0 ? c : 0.f, z >= 1 ? a : 0.f));
    }
  }
  fence_async_smem();
  __syncwarp();
  if (lane == 0) mbar_arrive(sb + SM_BAR + 8 * B_PTDONE);
}

__device__ __forceinline__ void strip_transpose(uint32_t sb, int warp, int lane, int cta) {
  mbar_wait(sb + SM_BAR + 8 * B_STRIP, 0);
  const int g = lane >> 2, c = lane & 3;
  const bool mine = (g >> 2) == (cta & 1);
  const uint32_t dst = sb + CV_XS + (g & 3) * 4096 + c * 4 + warp * 512;
  uint32_t r[8][4];
#pragma unroll
  for (int i = 0; i < 8; i++) ldsm4t(sb + SM_STRIP + ((warp * 8 + i) * 32 + lane) * 16, r[i][0], r[i][1], r[i][2], r[i][3]);
  if (mine) {
#pragma unroll
    for (int i = 0; i < 8; i++)
#pragma unroll
      for (int k = 0; k < 4; k++) sts32(dst + i * 64 + k * 16, r[i][k]);
  }
  fence_async_smem();
  __syncwarp();
  if (lane == 0) mbar_arrive(sb + SM_BAR + 8 * B_STRIPDONE);
}

__device__ __forceinline__ void load_mu2(uint32_t (&q)[16], uint32_t a) {
#pragma unroll
  for (int h = 0; h < 2; h++) {
    q[8 * h + 2] = lds32(a + h * 256); q[8 * h] = lds32(a + h * 256 + 32); q[8 * h + 1] = lds32(a + h * 256 + 64);
    q[8 * h + 4] = lds32(a + h * 256 + 96); q[8 * h + 5] = lds32(a + h * 256 + 128);
  }
}
__device__ __forceinline__ void fix_mu(uint32_t (&q)[16], int h) { q[8 * h + 3] = q[8 * h]; q[8 * h + 6] = q[8 * h + 1]; q[8 * h + 7] = q[8 * h + 4]; }
#define MU2_GROUP(FN, ACC, Q, DB, SC0)                        \
  do {                                                        \
    fix_mu(Q, 0); fix_mu(Q, 1);                               \
    wg_fence();                                               \
    FN(ACC, Q[0], Q[1], Q[2], Q[3], (DB) + 2, SC0);           \
    FN(ACC, Q[4], Q[5], Q[6], Q[7], (DB), 1);                 \
    FN(ACC, Q[8], Q[9], Q[10], Q[11], (DB) - 8 + 2, 1);       \
    FN(ACC, Q[12], Q[13], Q[14], Q[15], (DB) - 8, 1);         \
    wg_commit();                                              \
  } while (0)
__device__ __forceinline__ void load_far(uint32_t (&q)[16], uint32_t a) {
  q[2] = lds32(a);
#pragma unroll
  for (int k = 0; k < 4; k++) { q[4 * k] = lds32(a + (2 * k + 1) * 32); q[4 * k + 1] = lds32(a + (2 * k + 2) * 32); }
}
#define FAR_GROUP(ACC, Q, DB, SC0)                                                        \
  do {                                                                                    \
    _Pragma("unroll") for (int k = 0; k < 4; k++) { Q[4 * k + 3] = Q[4 * k]; if (k) Q[4 * k + 2] = Q[4 * k - 3]; } \
    wg_fence();                                                                           \
    wg_cv_n16t(ACC, Q[0], Q[1], Q[2], Q[3], (DB) + 96, SC0);                              \
    wg_cv_n16t(ACC, Q[4], Q[5], Q[6], Q[7], (DB) + 64, 1);                                \
    wg_cv_n16t(ACC, Q[8], Q[9], Q[10], Q[11], (DB) + 32, 1);                              \
    wg_cv_n16t(ACC, Q[12], Q[13], Q[14], Q[15], (DB), 1);                                 \
    wg_commit();                                                                          \
  } while (0)

__device__ __forceinline__ uint32_t u_chunk(uint32_t base, int q) {
  const int qq = q + 64, row = qq >> 2;
  return base + row * 64 + (((qq & 3) ^ ((row >> 1) & 3)) << 4);
}

__device__ __forceinline__ void conv_phase(const Params& p, uint32_t sb, int layer, int w, int wp, int lane, int cta,
                                           float kinvA, float kinvB) {
  const int t = wp * 32 + lane, T = w * 128 + t;
  const uint32_t bar = sb + SM_BAR;
  if (layer == 0) bar_sync(4, 256);
  sts128(sb + CV_U + (w + 2 * (t >> 6)) * 5120 + (t & 63) * 16, make_uint4(0, 0, 0, 0));
  mbar_wait(bar + 8 * B_XSFULL, layer);
  TS(3 + 20 * layer);
  {
    uint4 v[4];
#pragma unroll
    for (int i = 0; i < 4; i++) v[i] = lds128(sb + CV_B97 + T * 64 + i * 16);
    const uint32_t sa = sb + SM_STAT + (T >> 1) * 16 + (T & 1) * 8192;
#pragma unroll
    for (int i = 0; i < 4; i++) {
      const float2 a = ln_finalize(__uint_as_float(v[i].x), __uint_as_float(v[i].y));
      const float2 b = ln_finalize(__uint_as_float(v[i].z), __uint_as_float(v[i].w));
      sts128(sa + i * 2048, make_uint4(__byte_perm(__float_as_uint(a.x), __float_as_uint(b.x), 0x7632), __float_as_uint(a.y), __float_as_uint(b.y), 0));
    }
    if (layer != 0) mbar_wait(bar + 8 * B_PTFULL, 0);
    bar_sync(4, 256);
  }
  {
    uint4 st[8], x[4];
#pragma unroll
    for (int i = 0; i < 8; i++) st[i] = lds128(sb + SM_STAT + t * 16 + i * 2048);
#pragma unroll
    for (int i = 0; i < 4; i++) x[i] = lds128(sb + CV_XS + (w + 2 * (i >> 1)) * 4096 + t * 32 + (i & 1) * 16);
#pragma unroll
    for (int i = 0; i < 4; i++) {
      const uint32_t xx[4] = {x[i].x, x[i].y, x[i].z, x[i].w};
      uint32_t hh[4];
#pragma unroll
      for (int k = 0; k < 4; k++) {
        const uint4 s4 = st[4 * (i & 1) + k];
        const uint32_t dd = bf2_sub(xx[k], s4.x);
        hh[k] = pack_h(bf_lo(dd) * __uint_as_float(s4.y), bf_hi(dd) * __uint_as_float(s4.z));
      }
      sts128(u_chunk(sb + CV_U + (w + 2 * (i >> 1)) * 5120, 2 * t + (i & 1)), make_uint4(hh[0], hh[1], hh[2], hh[3]));
    }
  }
  bar_sync(4, 256);
  {
    uint4 x[8];
#pragma unroll
    for (int k = 0; k < 8; k++) x[k] = lds128(u_chunk(sb + CV_U + (w + 2 * (k >> 2)) * 5120, t - 3 + (k & 3)));
#pragma unroll
    for (int v = 0; v < 2; v++) {
      float u[32];
#pragma unroll
      for (int k = 0; k < 4; k++) {
        float2 f;
        f = unpack_h(x[4 * v + k].x); u[8 * k] = f.x; u[8 * k + 1] = f.y;
        f = unpack_h(x[4 * v + k].y); u[8 * k + 2] = f.x; u[8 * k + 3] = f.y;
        f = unpack_h(x[4 * v + k].z); u[8 * k + 4] = f.x; u[8 * k + 5] = f.y;
        f = unpack_h(x[4 * v + k].w); u[8 * k + 6] = f.x; u[8 * k + 7] = f.y;
      }
      float s9[8], s7[8];
      s9[0] = ((u[4] + u[5]) + (u[6] + u[7])) + ((u[8] + u[9]) + (u[10] + u[11])) + u[12];
      s9[4] = ((u[8] + u[9]) + (u[10] + u[11])) + ((u[12] + u[13]) + (u[14] + u[15])) + u[16];
      s7[0] = ((u[13] + u[14]) + (u[15] + u[16])) + ((u[17] + u[18]) + u[19]);
      s7[4] = ((u[17] + u[18]) + (u[19] + u[20])) + ((u[21] + u[22]) + u[23]);
#pragma unroll
      for (int j = 1; j < 4; j++) {
        s9[j] = s9[j - 1] + (u[j + 12] - u[j + 3]); s9[j + 4] = s9[j + 3] + (u[j + 16] - u[j + 7]);
        s7[j] = s7[j - 1] + (u[j + 19] - u[j + 12]); s7[j + 4] = s7[j + 3] + (u[j + 23] - u[j + 16]);
      }
      const uint32_t off = (uint32_t)(t * 16) ^ (((t >> 3) & 1) << 4);
      const uint32_t ba = sb + CV_B97 + (w + 2 * v) * 4096 + off;
      sts128(ba, make_uint4(pack_h(s9[0], s9[1]), pack_h(s9[2], s9[3]), pack_h(s9[4], s9[5]), pack_h(s9[6], s9[7])));
      sts128(ba + 2048, make_uint4(pack_h(s7[0], s7[1]), pack_h(s7[2], s7[3]), pack_h(s7[4], s7[5]), pack_h(s7[6], s7[7])));
    }
  }
  fence_async_smem();
  bar_sync(1 + w, 128);
  TS(4 + 20 * layer);

  const int g = lane >> 2, c = lane & 3;
  bf16* xout = g_xT[layer == 0 ? 0 : 2];
  const uint32_t ex = sb + (w ? CV_E1 : CV_E0), y3 = ex + 8192;
  float ps[16], pq[16];
#pragma unroll
  for (int i = 0; i < 16; i++) { ps[i] = 0.f; pq[i] = 0.f; }
#pragma unroll 1
  for (int v = 0; v < 2; v++) {
    const int slot = w + 2 * v, ch = 4 * cta + slot;
    const float dsk = bf2f(p.Dsk[ch]);
    const uint32_t pa = sb + SM_PT + slot * (PTW * 4) + (64 + 16 * wp + g - 2 * c) * 4;
    const uint32_t ub = sb + CV_U + slot * 5120;
    const uint32_t du = desc_lo(ub + 16 * 64, 16);
    const uint32_t d9 = desc_lo(sb + CV_B97 + slot * 4096, 2048);
    float acc1[32], acc2[28], acc4[20], acc3[8];
#pragma unroll
    for (int i = 0; i < 32; i++) acc1[i] = 0.f;
#pragma unroll
    for (int i = 0; i < 28; i++) acc2[i] = 0.f;
#pragma unroll
    for (int i = 0; i < 20; i++) acc4[i] = 0.f;
#pragma unroll
    for (int i = 0; i < 8; i++) acc3[i] = 0.f;
    pin_regs(acc1); pin_regs(acc2); pin_regs(acc4); pin_regs(acc3);
    uint32_t qa[16], qb[16], qc[16];
    load_far(qb, pa + PAW * 4 - 7 * 32);
    load_far(qc, pa + (PAW + 128) * 4 - 7 * 32);
    load_mu2(qa, pa - 3 * 32);
    FAR_GROUP(acc3, qb, d9, 0);
    FAR_GROUP(acc3, qc, d9 + (2048 >> 4), 1);
    wg_wait<1>();
    load_mu2(qb, pa - 3 * 32 + 512);
    MU2_GROUP(wg_cv_n64, acc1, qa, du, 0);
    wg_wait<1>();
    load_mu2(qc, pa - 3 * 32 + 1024);
    MU2_GROUP(wg_cv_n64, acc1, qb, du - 16, 1);
    wg_wait<1>();
    load_mu2(qa, pa - 3 * 32 + 1536);
    MU2_GROUP(wg_cv_n64, acc1, qc, du - 32, 1);
    wg_wait<1>();
    load_mu2(qb, pa - 3 * 32 + 2048);
    MU2_GROUP(wg_cv_n56, acc2, qa, du + 32 - 48, 0);
    wg_wait<1>();
    load_mu2(qc, pa - 3 * 32 + 2560);
    MU2_GROUP(wg_cv_n56, acc2, qb, du + 32 - 64, 1);
    wg_wait<1>();
    load_mu2(qa, pa - 3 * 32 + 3072);
    MU2_GROUP(wg_cv_n56, acc2, qc, du + 32 - 80, 1);
    wg_wait<1>();
    load_mu2(qb, pa - 3 * 32 + 3584);
    MU2_GROUP(wg_cv_n40, acc4, qa, du + 96 - 96, 0);
    wg_wait<1>();
    qc[2] = lds32(pa - 96 + 4096); qc[0] = lds32(pa - 64 + 4096); qc[1] = lds32(pa - 32 + 4096); qc[4] = lds32(pa + 4096); qc[5] = lds32(pa + 32 + 4096);
    MU2_GROUP(wg_cv_n40, acc4, qb, du + 96 - 112, 1);
    fix_mu(qc, 0);
    wg_fence();
    wg_cv_n40(acc4, qc[0], qc[1], qc[2], qc[3], du + 96 - 128 + 2, 1);
    wg_cv_n40(acc4, qc[4], qc[5], qc[6], qc[7], du + 96 - 128, 1);
    wg_commit();
    wg_wait<0>();
    pin_regs(acc1); pin_regs(acc2); pin_regs(acc4); pin_regs(acc3);
    TS(5 + 2 * v + 20 * layer);

#pragma unroll
    for (int i = 0; i < 28; i++) acc1[4 + i] += acc2[i];
#pragma unroll
    for (int i = 0; i < 20; i++) acc1[12 + i] += acc4[i];
    if (wp >= 2) {
      const int src = (lane & ~3) | ((c + 3) & 3);
#pragma unroll
      for (int nb = 7; nb >= 0; nb--)
#pragma unroll
        for (int hh = 0; hh < 2; hh++) {
          const float cur1 = acc1[4 * nb + 2 * hh + 1];
          const float prev1 = nb ? acc1[4 * (nb - 1) + 2 * hh + 1] : 0.f;
          const float sh = __shfl_sync(0xffffffffu, c == 3 ? prev1 : cur1, src);
          acc1[4 * nb + 2 * hh + 1] = acc1[4 * nb + 2 * hh];
          acc1[4 * nb + 2 * hh] = sh;
        }
    }
    {
      const uint32_t ea = ex + (wp >> 1) * 4096 + (wp & 1) * 2048 + lane * 8;
#pragma unroll
      for (int j = 0; j < 8; j++) {
        const float a = wp >= 2 ? acc1[2 * j] : acc1[16 + 2 * j], b = wp >= 2 ? acc1[2 * j + 1] : acc1[16 + 2 * j + 1];
        stsf2(ea + j * 256, a, b);
      }
#pragma unroll
      for (int nb = 0; nb < 2; nb++)
#pragma unroll
        for (int hh = 0; hh < 2; hh++) {
          const int z = 16 * (16 * wp + g + 8 * hh) + 8 * nb + 2 * c;
          stsf2(y3 + (z ^ (((z >> 6) & 3) << 3)) * 4, acc3[4 * nb + 2 * hh], acc3[4 * nb + 2 * hh + 1]);
        }
    }
    bar_sync(1 + w, 128);
    {
      const float kinv = v ? kinvB : kinvA;
      const int hi = wp >> 1, wq = wp & 1;
      float yv[16];
      const uint32_t ea = ex + (hi ^ 1) * 4096 + wq * 2048 + lane * 8;
#pragma unroll
      for (int j = 0; j < 8; j++) {
        const float2 e = ldsf2(ea + j * 256);
        yv[2 * j] = e.x + (hi ? acc1[16 + 2 * j] : acc1[2 * j]);
        yv[2 * j + 1] = e.y + (hi ? acc1[16 + 2 * j + 1] : acc1[2 * j + 1]);
      }
      if (hi) {
#pragma unroll
        for (int j = 0; j < 16; j++) {
          const int z = 32 * (8 * (j >> 2) + 2 * c + (j & 1)) + 16 * wq + g + 8 * ((j >> 1) & 1);
          yv[j] += ldsf(y3 + (z ^ (((z >> 6) & 3) << 3)) * 4);
        }
      }
      const int mat = lane >> 3, ib = 32 * hi + (lane & 7) + 8 * (mat >> 1), r8 = 2 * wq + (mat & 1);
      uint32_t xr[8], ur[8];
#pragma unroll
      for (int h2 = 0; h2 < 2; h2++) {
        const int i = ib + 16 * h2;
        ldsm4t(sb + CV_XS + slot * 4096 + i * 64 + r8 * 16, xr[4 * h2], xr[4 * h2 + 1], xr[4 * h2 + 2], xr[4 * h2 + 3]);
        ldsm4t(u_chunk(ub, 4 * i + r8), ur[4 * h2], ur[4 * h2 + 1], ur[4 * h2 + 2], ur[4 * h2 + 3]);
      }
      uint32_t o[8];
#pragma unroll
      for (int j = 0; j < 8; j++) {
        const uint32_t yy = pack_bf(yv[2 * j] * kinv, yv[2 * j + 1] * kinv);
        const float2 uf = unpack_h(ur[j]);
        o[j] = bf2_add(xr[j], bf2_add(yy, pack_bf(uf.x * dsk, uf.y * dsk)));
      }
      const uint32_t ob = sb + CV_B97 + slot * 4096;
#pragma unroll
      for (int h2 = 0; h2 < 2; h2++) {
        const int i = ib + 16 * h2;
        stsm4t(ob + i * 64 + ((r8 ^ ((i >> 1) & 3)) << 4), o[4 * h2], o[4 * h2 + 1], o[4 * h2 + 2], o[4 * h2 + 3]);
      }
      bar_sync(1 + w, 128);
      const int i = t >> 1, c0 = (t & 1) * 2;
      const uint4 o0 = lds128(ob + i * 64 + ((c0 ^ ((i >> 1) & 3)) << 4)), o1 = lds128(ob + i * 64 + (((c0 + 1) ^ ((i >> 1) & 3)) << 4));
      uint4* dst = reinterpret_cast<uint4*>(xout + ch * SEQ + t * 16);
      dst[0] = o0;
      dst[1] = o1;
      __syncwarp();
      if (lane == 0) mbar_arrive(bar + 8 * (B_PUB + w));
      const uint32_t oo[8] = {o0.x, o0.y, o0.z, o0.w, o1.x, o1.y, o1.z, o1.w};
#pragma unroll
      for (int k = 0; k < 8; k++) {
        const float lo = bf_lo(oo[k]), hi2 = bf_hi(oo[k]);
        ps[2 * k] += lo; pq[2 * k] = fmaf(lo, lo, pq[2 * k]);
        ps[2 * k + 1] += hi2; pq[2 * k + 1] = fmaf(hi2, hi2, pq[2 * k + 1]);
      }
    }
    TS(6 + 2 * v + 20 * layer);
  }
  fence_async_smem();
  __syncwarp();
  if (lane == 0) mbar_arrive(bar + 8 * B_CONVDONE);
  const uint32_t sa = sb + SM_MISC + t * 128;
  if (w == 1) {
#pragma unroll
    for (int i = 0; i < 8; i++)
      sts128(sa + ((i ^ (t & 7)) << 4), make_uint4(__float_as_uint(ps[2 * i]), __float_as_uint(pq[2 * i]), __float_as_uint(ps[2 * i + 1]), __float_as_uint(pq[2 * i + 1])));
    bar_arrive(4, 256);
  } else {
    bar_sync(4, 256);
#pragma unroll
    for (int i = 0; i < 8; i++) {
      const uint32_t a = sa + ((i ^ (t & 7)) << 4);
      const uint4 o4 = lds128(a);
      sts128(a, make_uint4(__float_as_uint(ps[2 * i] + __uint_as_float(o4.x)), __float_as_uint(pq[2 * i] + __uint_as_float(o4.y)),
                           __float_as_uint(ps[2 * i + 1] + __uint_as_float(o4.z)), __float_as_uint(pq[2 * i + 1] + __uint_as_float(o4.w))));
    }
    fence_async_smem();
    __syncwarp();
    if (lane == 0) mbar_arrive(bar + 8 * B_STAGED);
  }
}

struct RowC { float a1[2], b1[2], r[2], rm[2]; };

struct CsV { float2 g[2], u[2]; };
__device__ __forceinline__ void g1_ldcs(CsV& c, uint32_t csa) {
#pragma unroll
  for (int j = 0; j < 2; j++) { c.g[j] = ldsf2(csa + j * 32); c.u[j] = ldsf2(csa + 176 * 4 + j * 32); }
}
__device__ __forceinline__ void g1_slice(float (&prv)[64], const CsV& c, const RowC& rc, uint32_t* hp) {
  float e[8], u[8];
#pragma unroll
  for (int i = 0; i < 8; i++) {
    const int j = i >> 2, hh = (i >> 1) & 1;
    e[i] = 1.f + ex2f(fmaf(prv[i], rc.a1[hh], ((i & 1) ? c.g[j].y : c.g[j].x) * rc.b1[hh]));
    u[i] = fmaf(prv[32 + i], rc.r[hh], ((i & 1) ? c.u[j].y : c.u[j].x) * rc.rm[hh]);
  }
#pragma unroll
  for (int i = 0; i < 4; i++) hp[(i >> 1) * 256 + (i & 1) * 32] = pack_bf(u[2 * i] * rcpf(e[2 * i]), u[2 * i + 1] * rcpf(e[2 * i + 1]));
#pragma unroll
  for (int i = 0; i < 24; i++) { prv[i] = prv[i + 8]; prv[32 + i] = prv[40 + i]; }
  pin_regs(prv);
}

struct Ring { uint32_t st, ph; };
template <int NV, bool XW>
__device__ __forceinline__ void g1_mma2(float (&acc)[64], uint32_t bar, uint32_t da, uint32_t dw, int kb, const Ring& rg, bool l0, int layer) {
#pragma unroll
  for (int h = 0; h < 2; h++) {
    if (XW) mbar_wait_fast(bar + 8 * B_XFULL + 8 * (kb + h), layer);
    mbar_wait_fast(bar + 8 * B_WFULL + 8 * (rg.st + h), rg.ph);
    const uint32_t a = da + h * 1024, b = dw + (rg.st + h) * 1024;
    wg_fence();
#pragma unroll
    for (int k = 0; k < 4; k++) {
      if (NV == 0) wg_g1_n128(acc, a + k * 128, b + k * 128, (h | k) ? 1 : kb);
      else wg_g1_n112(acc, a + k * 128, b + k * 128, (h | k) ? 1 : kb);
    }
    wg_commit();
    if (h == 0) {
      wg_wait<1>();
      if (l0 && kb > 0) mbar_arrive(bar + 8 * B_WEMPTY + 8 * (rg.st ? rg.st - 1 : 5));
    }
  }
}
__device__ __forceinline__ void g1_release(uint32_t bar, bool l0, Ring& rg) {
  wg_wait<1>();
  if (l0) mbar_arrive(bar + 8 * B_WEMPTY + 8 * rg.st);
  rg.st += 2;
  if (rg.st == 6) { rg.st = 0; rg.ph ^= 1; }
}
template <int NV>
__device__ __forceinline__ void g1_part(float (&acc)[64], float (&prv)[64], uint32_t bar, uint32_t dx, uint32_t dw, int w, bool l0, Ring& rg,
                                        uint32_t csa, const RowC& rc, uint32_t* hp) {
  if (w == 1) bar_sync(6, 256);
#pragma unroll 1
  for (int kb = 0; kb < 8; kb += 2) {
    CsV c;
    g1_ldcs(c, csa + kb * 32);
    TRS(NV * 32 + 32 + kb * 4);
    g1_mma2<NV, false>(acc, bar, dx + kb * 1024, dw, kb, rg, l0, 0);
    if (w == 0 && kb == 0) bar_arrive(6, 256);
    TRS(NV * 32 + 32 + kb * 4 + 2);
    g1_slice(prv, c, rc, hp + kb * 256);
    TRS(NV * 32 + 32 + kb * 4 + 3);
    g1_release(bar, l0, rg);
    TRS(NV * 32 + 32 + kb * 4 + 4);
  }
}
__device__ __forceinline__ void g1_handover(float (&acc)[64], float (&prv)[64], uint32_t bar, bool l0, const Ring& rg) {
  wg_wait<0>();
  pin_regs(acc);
  if (l0) mbar_arrive(bar + 8 * B_WEMPTY + 8 * (rg.st ? rg.st - 1 : 5));
#pragma unroll
  for (int i = 0; i < 64; i++) prv[i] = acc[i];
  pin_regs(prv);
}

__device__ __forceinline__ void gemm1_phase(uint32_t sb, int layer, int w, int wp, int lane, int ti, int tj) {
  const uint32_t bar = sb + SM_BAR;
  const bool l0 = lane == 0;
  float acc[64], prv[64];
#pragma unroll
  for (int i = 0; i < 64; i++) acc[i] = 0.f;
  pin_regs(acc);
  const uint32_t dx = desc_lo(sb + SM_X + w * 8192, 1024), dw = desc_lo(sb + SM_WR, 8192);
  Ring rg; rg.st = 0; rg.ph = 0;
#pragma unroll 1
  for (int kb = 0; kb < 8; kb += 2) {
    TRS(kb * 4);
    g1_mma2<0, true>(acc, bar, dx + kb * 1024, dw, kb, rg, l0, layer);
    if (kb == 0) TS(9 + 20 * layer);
    if (kb == 4) TS(18 + 20 * layer);
    TRS(kb * 4 + 2);
    g1_release(bar, l0, rg);
    TRS(kb * 4 + 4);
  }
  RowC rc;
  uint32_t* hp = reinterpret_cast<uint32_t*>(g_h) + ((2 * ti + w) * 24 + tj) * 2048 + 2 * wp * 32 + lane;
  const uint32_t csa = sb + SM_CS + 2 * (lane & 3) * 4;
  g1_handover(acc, prv, bar, l0, rg);
  TS(10 + 20 * layer);
  mbar_wait(bar + 8 * B_STFULL, layer);
  if (layer == 0) mbar_wait(bar + 8 * B_CSFULL, 0);
#pragma unroll
  for (int hh = 0; hh < 2; hh++) {
    const float2 mr = ldsf2(sb + SM_ST + (w * 64 + 16 * wp + (lane >> 2) + 8 * hh) * 8);
    rc.a1[hh] = -1.4426950408889634f * mr.y; rc.b1[hh] = 1.4426950408889634f * mr.y * mr.x;
    rc.r[hh] = mr.y; rc.rm[hh] = -mr.y * mr.x;
  }
  g1_part<0>(acc, prv, bar, dx, dw, w, l0, rg, csa, rc, hp);
  __syncwarp();
  if (l0) mbar_arrive(bar + 8 * (B_PUB + w));
  g1_handover(acc, prv, bar, l0, rg);
  TS(11 + 20 * layer);
  g1_part<1>(acc, prv, bar, dx, dw, w, l0, rg, csa + 256, rc, hp + 8 * 2048);
  __syncwarp();
  if (l0) mbar_arrive(bar + 8 * (B_PUB + w));
  g1_handover(acc, prv, bar, l0, rg);
  if (l0) mbar_arrive(bar + 8 * B_G1DONE);
  TS(12 + 20 * layer);
  const int nbv = tj < 7 ? 6 : 2;
#pragma unroll 1
  for (int kb = 0; kb < nbv; kb += 2) {
    CsV c;
    g1_ldcs(c, csa + 512 + kb * 32);
    g1_slice(prv, c, rc, hp + 16 * 2048 + kb * 256);
  }
  __syncwarp();
  if (l0) mbar_arrive(bar + 8 * (B_PUB + w));
  TS(13 + 20 * layer);
}

__device__ __forceinline__ void gemm2_phase(const Params& p, uint32_t sb, int layer, int w, int wp, int lane, int tt, int tq) {
  const uint32_t bar = sb + SM_BAR;
  float acc[32];
#pragma unroll
  for (int i = 0; i < 32; i++) acc[i] = 0.f;
  pin_regs(acc);
  uint32_t stage = 0, phase = (layer * 3) & 1;
#pragma unroll 1
  for (int n = 0; n < 12; n++) {
    TR(256 + n * 4);
    mbar_wait_fast(bar + 8 * (B_G2FULL + stage), phase);
    TR(256 + n * 4 + 1);
    if (n == 0) TS(14 + 20 * layer);
    if (n == 8) TS(19 + 20 * layer);
    const uint32_t sa = sb + g2_stage_off(stage);
    const uint32_t da = desc_lo(sa + w * 8192, 1024), db = desc_lo(sa + 32768, 1024);
    if (n < 8) {
      wg_fence();
#pragma unroll
      for (int k = 0; k < 4; k++) wg_g2_n64(acc, da + k * 128, db + k * 128, (n | k) != 0);
#pragma unroll
      for (int k = 0; k < 4; k++) wg_g2_n64(acc, da + 1024 + k * 128, db + 512 + k * 128, 1);
      wg_commit();
    } else if (n < 11) {
      wg_fence();
#pragma unroll
      for (int k = 0; k < 3; k++) wg_g2_n64(acc, da + k * 128, db + k * 128, 1);
#pragma unroll
      for (int k = 0; k < 3; k++) wg_g2_n64(acc, da + 1024 + k * 128, db + 512 + k * 128, 1);
      wg_commit();
    } else {
      wg_fence();
#pragma unroll
      for (int k = 0; k < 3; k++) wg_g2_n64(acc, da + k * 128, db + k * 128, 1);
      wg_g2_n64(acc, da + 1024, db + 512, 1);
      wg_commit();
    }
    TR(256 + n * 4 + 2);
    wg_wait<1>();
    TR(256 + n * 4 + 3);
    if (n > 0 && lane == 0) mbar_arrive(bar + 8 * (B_G2EMPTY + ((stage + 3) & 3)));
    if (++stage == 4) { stage = 0; phase ^= 1; }
  }
  wg_wait<0>();
  pin_regs(acc);
  if (lane == 0) mbar_arrive(bar + 8 * (B_G2EMPTY + 3));
  TS(15 + 20 * layer);
  mbar_wait(bar + 8 * B_RESFULL, layer);
  const int t = wp * 32 + lane, g = lane >> 2, c = lane & 3;
  const int mat = lane >> 3;
  const int rrow = 64 * w + 16 * wp + (lane & 7) + 8 * (mat & 1);
  const uint32_t ra = sb + SM_RES + rrow * 128;
  uint32_t o[16];
#pragma unroll
  for (int nb = 0; nb < 8; nb += 2) {
    uint32_t r0, r1, r2, r3;
    ldsm4(ra + (((nb + (mat >> 1)) ^ (rrow & 7)) << 4), r0, r1, r2, r3);
    const uint32_t rr[4] = {r0, r1, r2, r3};
#pragma unroll
    for (int k = 0; k < 4; k++) {
      const int a = 4 * (nb + (k >> 1)) + 2 * (k & 1);
      o[2 * nb + k] = bf2_add(rr[k], pack_bf(acc[a], acc[a + 1]));
    }
  }
  if (layer == 0) {
#pragma unroll
    for (int nb = 0; nb < 8; nb += 2)
      stsm4(ra + (((nb + (mat >> 1)) ^ (rrow & 7)) << 4), o[2 * nb], o[2 * nb + 1], o[2 * nb + 2], o[2 * nb + 3]);
    __syncwarp();
#pragma unroll
    for (int i = 0; i < 4; i++) {
      const int idx = lane + 32 * i, row = 64 * w + 16 * wp + (idx >> 3), ch = idx & 7;
      const uint4 v = lds128(sb + SM_RES + row * 128 + ((ch ^ (row & 7)) << 4));
      *reinterpret_cast<uint4*>(g_xT[1] + (128 * tq + row) * SEQ + 64 * tt + 8 * ch) = v;
    }
    float v[32];
#pragma unroll
    for (int nb = 0; nb < 8; nb++) {
      const uint32_t a = o[2 * (nb & ~1) + 2 * (nb & 1)], b = o[2 * (nb & ~1) + 2 * (nb & 1) + 1];
      const float a0 = bf_lo(a), a1 = bf_hi(a), b0 = bf_lo(b), b1 = bf_hi(b);
      v[4 * nb] = a0 + b0; v[4 * nb + 1] = a1 + b1;
      v[4 * nb + 2] = fmaf(a0, a0, b0 * b0); v[4 * nb + 3] = fmaf(a1, a1, b1 * b1);
    }
    const bool s4 = lane & 16, s3 = lane & 8, s2 = lane & 4;
#pragma unroll
    for (int i = 0; i < 16; i++) {
      const float snd = s4 ? v[i] : v[16 + i], kp = s4 ? v[16 + i] : v[i];
      v[i] = kp + __shfl_xor_sync(0xffffffffu, snd, 16);
    }
#pragma unroll
    for (int i = 0; i < 8; i++) {
      const float snd = s3 ? v[i] : v[8 + i], kp = s3 ? v[8 + i] : v[i];
      v[i] = kp + __shfl_xor_sync(0xffffffffu, snd, 8);
    }
#pragma unroll
    for (int i = 0; i < 4; i++) {
      const float snd = s2 ? v[i] : v[4 + i], kp = s2 ? v[4 + i] : v[i];
      v[i] = kp + __shfl_xor_sync(0xffffffffu, snd, 4);
    }
    {
      const int nbf = (s4 ? 4 : 0) + (s3 ? 2 : 0) + (s2 ? 1 : 0), col = 8 * nbf + 2 * c;
      const uint32_t scr = sb + SM_G2S + (w * 4 + wp) * 512 + col * 8;
      stsf2(scr, v[0], v[2]);
      stsf2(scr + 8, v[1], v[3]);
    }
    bar_sync(4, 256);
    if (w == 0) {
      float s = 0.f;
#pragma unroll
      for (int k = 0; k < 8; k++) s += ldsf(sb + SM_G2S + k * 512 + t * 4);
      atomicAdd(reinterpret_cast<float*>(g_stat3) + 128 * tt + t, s);
    }
    __syncwarp();
    if (lane == 0) mbar_arrive(bar + 8 * (B_PUB + w));
    fence_async_smem();
    __syncwarp();
    if (lane == 0) mbar_arrive(bar + 8 * B_G2DONE);
  } else {
    const uint32_t oa = sb + SM_G2S + w * 8192;
#pragma unroll
    for (int nb = 0; nb < 8; nb += 2) {
      const int l = 8 * (nb + (mat >> 1)) + (lane & 7), chunk = 2 * wp + (mat & 1);
      stsm4t(oa + l * 128 + ((chunk ^ (l & 7)) << 4), o[2 * nb], o[2 * nb + 1], o[2 * nb + 2], o[2 * nb + 3]);
    }
    bar_sync(1 + w, 128);
#pragma unroll
    for (int i = 0; i < 4; i++) {
      const int idx = t + 128 * i, l = idx >> 3, ch = idx & 7;
      const uint4 v = lds128(oa + l * 128 + ((ch ^ (l & 7)) << 4));
      *reinterpret_cast<uint4*>(p.out + (64 * tt + l) * DM + 128 * tq + 64 * w + 8 * ch) = v;
    }
  }
  TS(16 + 20 * layer);
  (void)g;
}

__global__ void __launch_bounds__(NTHR, 1)
fused_s4d_glu_kernel(const __grid_constant__ CUtensorMap tmG, const __grid_constant__ CUtensorMap tmU, const __grid_constant__ CUtensorMap tmWd,
                     const __grid_constant__ CUtensorMap tmX1, const __grid_constant__ CUtensorMap tmX3,
                     const __grid_constant__ CUtensorMap tmR1, const __grid_constant__ CUtensorMap tmR3,
                     const __grid_constant__ CUtensorMap tmX0, const Params p) {
  extern __shared__ __align__(1024) unsigned char smem[];
  const uint32_t sb = smem_u32(smem);
  const uint32_t bar = sb + SM_BAR;
  const int tid = threadIdx.x, lane = tid & 31;
  const int warp = __shfl_sync(0xffffffffu, tid >> 5, 0);
  const int cta = blockIdx.x;
  const int grp = cta >> 4, r16 = cta & 15;
  const int ti = 4 * (grp & 3) + (r16 & 3), tj = 4 * (grp >> 2) + (r16 >> 2);
  const int tt = 4 * grp + (r16 >> 2), tq = r16 & 3;

  uint32_t kraw[10];
  if (warp < 8) {
#pragma unroll
    for (int v = 0; v < 2; v++) {
      const int ch = 4 * cta + 2 * v + (warp >> 2), idx = ch * NMODE + (tid & 127);
      asm volatile("ld.global.nc.u16 %0, [%1];" : "=r"(kraw[5 * v]) : "l"(p.logA + idx));
      asm volatile("ld.global.nc.u16 %0, [%1];" : "=r"(kraw[5 * v + 1]) : "l"(p.Aim + idx));
      asm volatile("ld.global.nc.u16 %0, [%1];" : "=r"(kraw[5 * v + 2]) : "l"(p.Cre + idx));
      asm volatile("ld.global.nc.u16 %0, [%1];" : "=r"(kraw[5 * v + 3]) : "l"(p.Cim + idx));
      asm volatile("ld.global.nc.u16 %0, [%1];" : "=r"(kraw[5 * v + 4]) : "l"(p.logdt + ch));
    }
  }
  if (tid == 0) {
    if (sb & 1023) __trap();
    for (int i = 0; i < 6; i++) { mbar_init(bar + 8 * (B_WFULL + i), 1); mbar_init(bar + 8 * (B_WEMPTY + i), 8); }
    for (int i = 0; i < 8; i++) mbar_init(bar + 8 * (B_XFULL + i), 1);
    for (int i = 0; i < 4; i++) { mbar_init(bar + 8 * (B_G2FULL + i), 1); mbar_init(bar + 8 * (B_G2EMPTY + i), 8); }
    mbar_init(bar + 8 * B_CSFULL, 1); mbar_init(bar + 8 * B_RESFULL, 1); mbar_init(bar + 8 * B_PTFULL, 1); mbar_init(bar + 8 * B_XSFULL, 1);
    mbar_init(bar + 8 * B_CONVDONE, 8); mbar_init(bar + 8 * B_G1DONE, 8); mbar_init(bar + 8 * B_G2DONE, 8);
    mbar_init(bar + 8 * B_TAILDONE, 1); mbar_init(bar + 8 * B_STAGED, 4); mbar_init(bar + 8 * B_STFULL, 1); mbar_init(bar + 8 * B_KGDONE, 8); mbar_init(bar + 8 * B_STRIP, 1); mbar_init(bar + 8 * B_STRIPDONE, 8); mbar_init(bar + 8 * B_PTDONE, 8); mbar_init(bar + 8 * B_PTSAVED, 1);
    mbar_init(bar + 8 * B_PUB, 4); mbar_init(bar + 8 * (B_PUB + 1), 4);
    asm volatile("fence.mbarrier_init.release.cluster;" ::: "memory");
    fence_async_smem();
  }
  __syncthreads();

  if (warp < 8) {
    asm volatile("setmaxnreg.inc.sync.aligned.u32 224;");
    TS(0);
    const int w = warp >> 2, wp = warp & 3;
    const int t = wp * 32 + lane;
    KParam kp[2];
#pragma unroll
    for (int v = 0; v < 2; v++) {
      uint32_t f[5];
#pragma unroll
      for (int k = 0; k < 5; k++) asm volatile("shl.b32 %0, %1, 16;" : "=r"(f[k]) : "r"(kraw[5 * v + k]));
      kp[v].logA = __uint_as_float(f[0]); kp[v].aim = __uint_as_float(f[1]); kp[v].cre = __uint_as_float(f[2]);
      kp[v].cim = __uint_as_float(f[3]); kp[v].logdt = __uint_as_float(f[4]);
    }
    float kinv[2];
    kgen(sb, w, wp, lane, kp, kinv);
    strip_transpose(sb, warp, lane, cta);
    TS(1);
#pragma unroll 1
    for (int layer = 0; layer < 2; layer++) {
      conv_phase(p, sb, layer, w, wp, lane, cta, kinv[0], kinv[1]);
      gemm1_phase(sb, layer, w, wp, lane, ti, tj);
      gemm2_phase(p, sb, layer, w, wp, lane, tt, tq);
    }
  } else {
    asm volatile("setmaxnreg.dec.sync.aligned.u32 56;");
    const int wv = warp - 8;
    unsigned ep1;
    asm volatile("ld.relaxed.gpu.global.u32 %0, [%1];" : "=r"(ep1) : "l"(&g_epoch) : "memory");
    ep1 += 1;
    {
      uint4 v[8];
#pragma unroll
      for (int r = 0; r < 4; r++) {
        const bf16* src = p.x0 + (16 * cta + 4 * wv + r) * DM + lane * 8;
        v[2 * r] = ldg128_nc(src); v[2 * r + 1] = ldg128_nc(src + 256);
      }
      if (wv == 0 && elect_one()) {
        const uint32_t fb = bar + 8 * B_STRIP;
        mbar_expect(fb, 32768);
#pragma unroll 1
        for (int k = 0; k < 8; k++) tma_2d(sb + SM_STRIP + k * 4096, &tmX0, 8 * (cta >> 1), 256 * k, fb);
        tmap_prefetch(&tmG); tmap_prefetch(&tmU); tmap_prefetch(&tmX1); tmap_prefetch(&tmWd);
        tmap_prefetch(&tmR1); tmap_prefetch(&tmX3); tmap_prefetch(&tmR3);
        l2_prefetch(reinterpret_cast<const char*>(p.wd) + cta * 11008, 11008);
      }
      __syncwarp();
      if (lane < 9) {
        float2* z = (lane == 0 ? g_stat3 : g_stat2[(lane - 1) >> 2][(lane - 1) & 3]) + 16 * cta + 4 * wv;
        *reinterpret_cast<uint4*>(z) = make_uint4(0, 0, 0, 0);
        *reinterpret_cast<uint4*>(z + 2) = make_uint4(0, 0, 0, 0);
      }
      float a[8];
#pragma unroll
      for (int r = 0; r < 4; r++) {
        const uint32_t xx[8] = {v[2 * r].x, v[2 * r].y, v[2 * r].z, v[2 * r].w, v[2 * r + 1].x, v[2 * r + 1].y, v[2 * r + 1].z, v[2 * r + 1].w};
        float s0 = 0.f, s1 = 0.f, q0 = 0.f, q1 = 0.f;
#pragma unroll
        for (int k = 0; k < 8; k++) { const float lo = bf_lo(xx[k]), hi = bf_hi(xx[k]); s0 += lo; s1 += hi; q0 = fmaf(lo, lo, q0); q1 = fmaf(hi, hi, q1); }
        a[2 * r] = s0 + s1; a[2 * r + 1] = q0 + q1;
      }
      const bool s4 = lane & 16, s3 = lane & 8, s2 = lane & 4;
#pragma unroll
      for (int i = 0; i < 4; i++) { const float snd = s4 ? a[i] : a[4 + i], kp2 = s4 ? a[4 + i] : a[i]; a[i] = kp2 + __shfl_xor_sync(0xffffffffu, snd, 16); }
#pragma unroll
      for (int i = 0; i < 2; i++) { const float snd = s3 ? a[i] : a[2 + i], kp2 = s3 ? a[2 + i] : a[i]; a[i] = kp2 + __shfl_xor_sync(0xffffffffu, snd, 8); }
      { const float snd = s2 ? a[0] : a[1], kp2 = s2 ? a[1] : a[0]; a[0] = kp2 + __shfl_xor_sync(0xffffffffu, snd, 4); }
      a[0] += __shfl_xor_sync(0xffffffffu, a[0], 2);
      a[0] += __shfl_xor_sync(0xffffffffu, a[0], 1);
      if ((lane & 3) == 0) reinterpret_cast<float*>(g_stat1)[2 * (16 * cta + 4 * wv) + (lane >> 2)] = a[0];
      bar_sync(3, 128);
      if (wv == 0 && lane == 0) TSA(21);
    }
    if (wv == 3) {
      if (elect_one()) {
        mbar_wait(bar + 8 * B_PTDONE, 0);
        asm volatile("cp.async.bulk.global.shared::cta.bulk_group [%0], [%1], %2;" ::"l"(g_ptab + 4 * cta * PTW), "r"(sb + SM_PT), "n"(4 * PTW * 4) : "memory");
        asm volatile("cp.async.bulk.commit_group;" ::: "memory");
        asm volatile("cp.async.bulk.wait_group 0;" ::: "memory");
        fence_async_all();
        mbar_arrive(bar + 8 * B_PTSAVED);
      }
      __syncwarp();
      if (elect_one()) {
        flag_wait(&g_flag[F_CS * 8], ep1 * 172);
        fence_async_all();
        const uint32_t fb = bar + 8 * B_CSFULL;
        mbar_expect(fb, 1408);
        bulk_g2s(sb + SM_CS, g_cs + 176 * tj, 704, fb);
        bulk_g2s(sb + SM_CS + 704, g_cs + CSP + 176 * tj, 704, fb);
      }
      __syncwarp();
#pragma unroll 1
      for (int layer = 0; layer < 2; layer++) {
        if (elect_one()) {
          mbar_wait(bar + 8 * B_STAGED, layer);
          asm volatile("cp.reduce.async.bulk.global.shared::cta.bulk_group.add.f32 [%0], [%1], 16384;" ::"l"(g_stat2[layer][cta & 3]), "r"(sb + SM_MISC) : "memory");
          asm volatile("cp.async.bulk.commit_group;" ::: "memory");
          asm volatile("cp.async.bulk.wait_group.read 0;" ::: "memory");
          mbar_arrive(bar + 8 * B_TAILDONE);
          asm volatile("cp.async.bulk.wait_group 0;" ::: "memory");
          fence_async_all();
          flag_publish(&g_flag[(F_S + layer) * 8]);
          if (layer == 1) TSA(56);
          flag_wait(&g_flag[(F_S + layer) * 8], ep1 * 128);
          if (layer == 1) TSA(57);
        }
        __syncwarp();
#pragma unroll 1
        for (int k0 = 0; k0 < 4; k0 += 2) {
          float2 v[8];
#pragma unroll
          for (int k = 0; k < 2; k++) {
            const int l = 128 * ti + 32 * (k0 + k) + lane, tq16 = l >> 4;
            const float* src = reinterpret_cast<const float*>(g_stat2[layer]) + tq16 * 32 + ((((l & 15) >> 1) ^ (tq16 & 7)) << 2) + (l & 1) * 2;
#pragma unroll
            for (int r = 0; r < 4; r++) asm volatile("ld.global.cg.v2.f32 {%0, %1}, [%2];" : "=f"(v[4 * k + r].x), "=f"(v[4 * k + r].y) : "l"(src + r * 2 * SEQ) : "memory");
          }
#pragma unroll
          for (int k = 0; k < 2; k++) {
            const float2 mr = ln_finalize((v[4 * k].x + v[4 * k + 1].x) + (v[4 * k + 2].x + v[4 * k + 3].x), (v[4 * k].y + v[4 * k + 1].y) + (v[4 * k + 2].y + v[4 * k + 3].y));
            stsf2(sb + SM_ST + (32 * (k0 + k) + lane) * 8, mr.x, mr.y);
          }
        }
        __syncwarp();
        if (lane == 0) mbar_arrive(bar + 8 * B_STFULL);
      }
    } else if (wv == 1 || wv == 2) {
      const int unit = cta + 128 * (wv - 1);
      if (unit < 172) {
        const int mat = unit / 86, col0 = (unit - mat * 86) * 16 + (lane & 1) * 8;
        const bf16* wsrc = (mat ? p.wu : p.wg) + (lane >> 1) * FF + col0;
        float a[8];
#pragma unroll
        for (int k = 0; k < 8; k++) a[k] = 0.f;
#pragma unroll 1
        for (int b = 0; b < 4; b++) {
          uint4 v[8];
#pragma unroll
          for (int i = 0; i < 8; i++) v[i] = ldg128_nc(wsrc + (b * 8 + i) * 16 * FF);
#pragma unroll
          for (int i = 0; i < 8; i++) {
            a[0] += bf_lo(v[i].x); a[1] += bf_hi(v[i].x); a[2] += bf_lo(v[i].y); a[3] += bf_hi(v[i].y);
            a[4] += bf_lo(v[i].z); a[5] += bf_hi(v[i].z); a[6] += bf_lo(v[i].w); a[7] += bf_hi(v[i].w);
          }
        }
#pragma unroll
        for (int k = 0; k < 8; k++)
#pragma unroll
          for (int o = 2; o < 32; o <<= 1) a[k] += __shfl_xor_sync(0xffffffffu, a[k], o);
        if (lane < 2) {
          float4* dst = reinterpret_cast<float4*>(g_cs + mat * CSP + col0);
          dst[0] = make_float4(a[0], a[1], a[2], a[3]);
          dst[1] = make_float4(a[4], a[5], a[6], a[7]);
        }
        __syncwarp();
        if (elect_one()) { flag_publish(&g_flag[F_CS * 8]); if (wv == 1) TSA(41); }
        __syncwarp();
      }
      if (elect_one()) {
        const int w = wv - 1;
        uint32_t ph = 0;
        const uint32_t pb = bar + 8 * (B_PUB + w);
#pragma unroll 1
        for (int layer = 0; layer < 2; layer++) {
#pragma unroll 1
          for (int e = 0; e < (layer == 0 ? 6 : 5); e++) {
            mbar_wait(pb, ph);
            ph ^= 1;
            const int f = e < 2 ? F_1 + layer * 2 + e : (e < 5 ? F_2 + layer * 96 + (2 * ti + w) * 3 + (e - 2) : F_3);
            flag_publish(&g_flag[f * 8]);
          }
        }
      }
    } else if (elect_one()) {
      flag_publish(&g_flag[F_0 * 8]);
      TSA(22);
      uint32_t wst = 0, wph = 1;
      auto issue_w = [&](int n) {
        TRA(n * 4);
        mbar_wait(bar + 8 * (B_WEMPTY + wst), wph);
        const uint32_t fb = bar + 8 * (B_WFULL + wst), dst = sb + SM_WR + wst * 16384;
        const int f0 = 176 * tj + 8 * (n & ~7);
        mbar_expect(fb, 16384);
        tma_4d(dst, &tmG, f0, 0, (n >> 2) & 1, 32 * (n & 3), fb);
        tma_4d(dst + 8192, &tmU, f0, 0, (n >> 2) & 1, 32 * (n & 3), fb);
        TRA(n * 4 + 2);
        if (++wst == 6) { wst = 0; wph ^= 1; }
      };
#pragma unroll 1
      for (int layer = 0; layer < 2; layer++) {
        const CUtensorMap* tmX = layer ? &tmX3 : &tmX1;
        issue_w(0);
        if (layer) { issue_w(1); issue_w(2); }
        {
          flag_wait(&g_flag[(layer ? F_3 : F_0) * 8], ep1 * (layer ? 256 : 128));
          TSA(layer ? 48 : 40);
          fence_async_all();
          const uint32_t fb = bar + 8 * B_XSFULL;
          if (layer == 0) {
            if (cta == 0) asm volatile("st.relaxed.gpu.global.u32 [%0], %1;" ::"l"(&g_epoch), "r"(ep1) : "memory");
            mbar_wait(bar + 8 * B_KGDONE, 0);
            mbar_expect(fb, 16384);
          } else {
            mbar_expect(fb, 32768);
            bulk_g2s(sb + CV_XS, g_xT[1] + 4 * cta * SEQ, 16384, fb);
          }
          bulk_g2s(sb + CV_B97, layer ? g_stat3 : g_stat1, 16384, fb);
          if (layer == 0) {
            mbar_wait(bar + 8 * B_STRIPDONE, 0);
            issue_w(1);
            issue_w(2);
          }
        }
#pragma unroll 1
        for (int b = 0; b < 2; b++) {
          if (b == 1) {
            TSA(42 + 8 * layer);
            mbar_wait(bar + 8 * B_CONVDONE, layer);
            if (layer == 0) mbar_wait(bar + 8 * B_PTSAVED, 0);
            issue_w(3);
            issue_w(4);
          }
          if (layer == 1 && b == 1) TSA(58);
          flag_wait(&g_flag[(F_1 + layer * 2 + b) * 8], ep1 * 256);
          if (layer == 1 && b == 1) TSA(59);
          fence_async_all();
#pragma unroll 1
          for (int k = 0; k < 4; k++) {
            const uint32_t fb = bar + 8 * (B_XFULL + 4 * b + k);
            mbar_expect(fb, 16384);
            tma_5d(sb + SM_X + (4 * b + k) * 16384, tmX, 0, 0, b, 32 * k, 2 * ti, fb);
          }
        }
        mbar_wait(bar + 8 * B_TAILDONE, layer);
        issue_w(5);
        TSA(43 + 8 * layer);
#pragma unroll 1
        for (int n = 6; n < 24; n++) issue_w(n);
        uint32_t st2 = 0, ph2 = ((layer * 3) & 1) ^ 1;
        const bf16* hsrc = g_h + tt * 24 * 4096;
        const unsigned* f2 = &g_flag[(F_2 + layer * 96 + tt * 3) * 8];
        flag_wait(f2, ep1 * 8);
        fence_async_all();
        TSA(45 + 8 * layer);
        mbar_wait(bar + 8 * (B_WEMPTY + 0), 1);
        mbar_wait(bar + 8 * (B_WEMPTY + 1), 1);
        mbar_wait(bar + 8 * (B_WEMPTY + 2), 1);
#pragma unroll 1
        for (int n = 0; n < 12; n++) {
          const int pp = n >> 2, j = 2 * (n & 3);
          const uint32_t fb = bar + 8 * (B_G2FULL + st2), dst = sb + g2_stage_off(st2);
          const uint32_t hbytes = pp < 2 ? 16384 : (j < 6 ? 14336 : 10240);
          if (n == 1) {
            mbar_wait(bar + 8 * B_G1DONE, layer);
            TSA(44 + 8 * layer);
            const uint32_t rb = bar + 8 * B_RESFULL;
            mbar_expect(rb, 16384);
            tma_2d(sb + SM_RES, layer ? &tmR3 : &tmR1, 64 * tt, 128 * tq, rb);
          }
          mbar_wait(bar + 8 * (B_G2EMPTY + st2), ph2);
          mbar_expect(fb, 32768 + hbytes);
          tma_3d(dst, &tmWd, 0, 176 * j + 64 * pp, 2 * tq, fb);
          tma_3d(dst + 16384, &tmWd, 0, 176 * j + 176 + 64 * pp, 2 * tq, fb);
          if (j == 0 && pp > 0) { flag_wait(f2 + pp * 8, ep1 * 8); fence_async_all(); TSA(45 + pp + 8 * layer); }
          bulk_g2s(dst + 32768, hsrc + n * 8192, hbytes, fb);
          if (++st2 == 4) { st2 = 0; ph2 ^= 1; }
        }
        if (layer == 0) {
          mbar_wait(bar + 8 * B_G2DONE, 0);
          const uint32_t fb = bar + 8 * B_PTFULL;
          mbar_expect(fb, 4 * PTW * 4);
          bulk_g2s(sb + SM_PT, g_ptab + 4 * cta * PTW, 4 * PTW * 4, fb);
        }
      }
    }
  }
}

typedef CUresult (*EncodeFn)(CUtensorMap*, CUtensorMapDataType, cuuint32_t, void*, const cuuint64_t*, const cuuint64_t*, const cuuint32_t*,
                             const cuuint32_t*, CUtensorMapInterleave, CUtensorMapSwizzle, CUtensorMapL2promotion, CUtensorMapFloatOOBfill);

void make_map(EncodeFn fn, CUtensorMap* m, const void* base, int rank, const cuuint64_t* dims, const cuuint64_t* strides, const cuuint32_t* box) {
  cuuint32_t es[5] = {1, 1, 1, 1, 1};
  fn(m, CU_TENSOR_MAP_DATA_TYPE_BFLOAT16, rank, const_cast<void*>(base), dims, strides, box, es, CU_TENSOR_MAP_INTERLEAVE_NONE,
     CU_TENSOR_MAP_SWIZZLE_128B, CU_TENSOR_MAP_L2_PROMOTION_L2_128B, CU_TENSOR_MAP_FLOAT_OOB_FILL_NONE);
}

}

extern "C" void kernel_launch(void* const* d_in, const int* in_sizes, int n_in, void* d_out, int out_size) {
  (void)in_sizes; (void)n_in; (void)out_size;
  static EncodeFn enc = nullptr;
  static bf16* xT = nullptr;
  if (!enc) {
    void* fn = nullptr;
    cudaDriverEntryPointQueryResult qr;
    cudaGetDriverEntryPoint("cuTensorMapEncodeTiled", &fn, cudaEnableDefault, &qr);
    enc = (EncodeFn)fn;
    void* a = nullptr;
    cudaGetSymbolAddress(&a, g_xT);
    xT = (bf16*)a;
    cudaFuncSetAttribute(fused_s4d_glu_kernel, cudaFuncAttributeMaxDynamicSharedMemorySize, SM_TOTAL);
  }
  Params p;
  p.x0 = (const bf16*)d_in[0]; p.logA = (const bf16*)d_in[1]; p.Aim = (const bf16*)d_in[2]; p.Cre = (const bf16*)d_in[3];
  p.Cim = (const bf16*)d_in[4]; p.logdt = (const bf16*)d_in[5]; p.Dsk = (const bf16*)d_in[6];
  p.wg = (const bf16*)d_in[8]; p.wu = (const bf16*)d_in[9]; p.wd = (const bf16*)d_in[10];
  p.out = (bf16*)d_out;

  CUtensorMap tmG, tmU, tmWd, tmX1, tmX3, tmR1, tmR3, tmX0;
  {
    const cuuint64_t dims[4] = {FF, 2, 2, 128}, str[3] = {FF * 2, FF * 4, FF * 8};
    const cuuint32_t box[4] = {64, 2, 1, 32};
    make_map(enc, &tmG, p.wg, 4, dims, str, box);
    make_map(enc, &tmU, p.wu, 4, dims, str, box);
  }
  {
    const cuuint64_t dims[3] = {64, FF, 8}, str[2] = {DM * 2, 128};
    const cuuint32_t box[3] = {64, 64, 2};
    make_map(enc, &tmWd, p.wd, 3, dims, str, box);
  }
  {
    const cuuint64_t dims[5] = {64, 2, 2, 128, 32}, str[4] = {SEQ * 2, SEQ * 4, SEQ * 8, 128};
    const cuuint32_t box[5] = {64, 2, 1, 32, 2};
    make_map(enc, &tmX1, xT, 5, dims, str, box);
    make_map(enc, &tmX3, xT + 2 * DM * SEQ, 5, dims, str, box);
  }
  {
    const cuuint64_t dims[2] = {SEQ, DM}, str[1] = {SEQ * 2};
    const cuuint32_t box[2] = {64, 128};
    make_map(enc, &tmR1, xT, 2, dims, str, box);
    make_map(enc, &tmR3, xT + 2 * DM * SEQ, 2, dims, str, box);
  }
  {
    const cuuint64_t dims[2] = {DM, SEQ}, str[1] = {DM * 2};
    const cuuint32_t box[2] = {8, 256}, es[2] = {1, 1};
    enc(&tmX0, CU_TENSOR_MAP_DATA_TYPE_BFLOAT16, 2, const_cast<bf16*>(p.x0), dims, str, box, es, CU_TENSOR_MAP_INTERLEAVE_NONE,
        CU_TENSOR_MAP_SWIZZLE_NONE, CU_TENSOR_MAP_L2_PROMOTION_L2_128B, CU_TENSOR_MAP_FLOAT_OOB_FILL_NONE);
  }
  fused_s4d_glu_kernel<<<NCTA, NTHR, SM_TOTAL, cudaStreamPerThread>>>(tmG, tmU, tmWd, tmX1, tmX3, tmR1, tmR3, tmX0, p);
}
```

```cpp
#include <cuda_runtime.h>
#include <cuda_bf16.h>
#include <cuda_fp16.h>
#include <cuda.h>
#include <stdint.h>

namespace {

typedef __nv_bfloat16 bf16;

constexpr int SEQ = 2048;
constexpr int DM = 512;
constexpr int NMODE = 128;
constexpr int FF = 1376;
constexpr int NCTA = 128;
constexpr int NTHR = 384;
constexpr int CSP = 1408;
constexpr int PAW = 1152;
constexpr int PTW = 1408;
constexpr int SPIN_LIMIT = 1 << 20;

constexpr uint32_t SM_X = 0;
constexpr uint32_t SM_WR = 131072;
constexpr uint32_t SM_MISC = 212992;
constexpr uint32_t SM_SMALL = 229376;
constexpr uint32_t SM_TOTAL = 232448;
constexpr uint32_t SM_CONV = 65536;
constexpr uint32_t CV_U = SM_CONV;
constexpr uint32_t CV_B97 = SM_CONV + 20480;
constexpr uint32_t CV_E0 = SM_CONV + 36864;
constexpr uint32_t CV_XS = SM_CONV + 49152;
constexpr uint32_t CV_E1 = SM_MISC;
constexpr uint32_t KG_A = 0;
constexpr uint32_t KG_B = 12288;
constexpr uint32_t SM_STRIP = SM_WR + 16384;
constexpr uint32_t SM_PT = SM_WR + 3 * 16384;
constexpr uint32_t SM_STAT = SM_MISC;
constexpr uint32_t SM_RES = 98304;
constexpr uint32_t SM_G2S = 114688;
constexpr uint32_t G2_STAGE = 32768;
constexpr uint32_t SM_XB = SM_WR;
constexpr uint32_t SM_XS2 = SM_WR + 32768;
constexpr uint32_t SM_BAR = SM_SMALL;
constexpr uint32_t SM_CS = SM_SMALL + 512;
constexpr uint32_t SM_ST = SM_SMALL + 1920;
constexpr uint32_t SM_ROLE = SM_SMALL + 2944;

enum {
  B_WFULL = 0, B_WEMPTY = 6, B_XFULL = 12, B_CSFULL = 20, B_G2FULL = 21, B_G2EMPTY = 27, B_RESFULL = 33,
  B_PTFULL = 34, B_XSFULL = 35, B_CONVDONE = 36, B_G1DONE = 37, B_G2DONE = 38, B_TAILDONE = 39, B_STFULL = 40, B_KDONE = 41, B_F0OK = 42,
  B_KGDONE = 43, B_STAGED = 44, B_STRIP = 45, B_STRIPDONE = 46, B_PTDONE = 47, B_PTSAVED = 48, B_PEERRDY = 49, B_RECV = 50, B_ROLE = 51, B_PUBDONE = 52,
  B_CSL = 57, B_CSDONE = 59, B_PUB3 = 60, B_B97 = 61,
  B_PUB = 53
};
constexpr int bar_log2_count(int i) {
  return (i >= B_WEMPTY && i < B_WEMPTY + 6) || (i >= B_G2EMPTY && i < B_G2EMPTY + 6) || i == B_CONVDONE || i == B_G1DONE || i == B_G2DONE ||
                 i == B_KGDONE || i == B_KDONE || i == B_STRIPDONE || i == B_PTDONE || i == B_PEERRDY
             ? 3
             : ((i >= B_PUB && i < B_PUB + 4) || i == B_STAGED || i == B_B97 ? 2 : (i == B_PUBDONE || i == B_CSDONE || i == B_PUB3 ? 1 : 0));
}
constexpr unsigned long long bar_codes(int base) {
  unsigned long long r = 0;
  for (int i = 0; i < 32; i++) r |= (unsigned long long)bar_log2_count(base + i) << (2 * i);
  return r;
}
constexpr unsigned long long LO_CODES = bar_codes(0), HI_CODES = bar_codes(32);
enum { F_0 = 0, F_CS = 1, F_3 = 2, F_S = 4, F_1 = 8, F_2 = 32, F_COUNT = 128 };

struct Scratch {
  bf16 xT[3][DM * SEQ];
  bf16 h[16 * 24 * 8192];
  uint32_t ptab[DM * PTW];
  float2 stat1[SEQ];
  float2 stat3[SEQ];
  float2 stat2[2][4][SEQ];
  float cs[2 * CSP];
  unsigned flag[F_COUNT * 8];
  unsigned tpc[64];
  unsigned epoch;
};
__device__ __align__(1024) Scratch g_scratch;

#define TS(k)
#define TSA(k)
#define TR(k)
#define TRA(k)
#define TRS(k)

struct Params {
  const bf16 *x0, *logA, *Aim, *Cre, *Cim, *logdt, *Dsk, *wg, *wu, *wd;
  bf16* out;
  Scratch* sc;
};

__device__ __forceinline__ uint32_t smem_u32(const void* p) { return (uint32_t)__cvta_generic_to_shared(p); }
__device__ __forceinline__ void mbar_init(uint32_t a, uint32_t c) { asm volatile("mbarrier.init.shared::cta.b64 [%0], %1;" ::"r"(a), "r"(c) : "memory"); }
__device__ __forceinline__ void mbar_expect(uint32_t a, uint32_t b) { asm volatile("mbarrier.arrive.expect_tx.shared::cta.b64 _, [%0], %1;" ::"r"(a), "r"(b) : "memory"); }
__device__ __forceinline__ void mbar_arrive(uint32_t a) { asm volatile("mbarrier.arrive.shared::cta.b64 _, [%0];" ::"r"(a) : "memory"); }
__device__ __forceinline__ void mbar_wait(uint32_t a, uint32_t par) {
  asm volatile("{\n.reg .pred p;\nLW:\nmbarrier.try_wait.parity.shared::cta.b64 p, [%0], %1;\n@!p bra LW;\n}\n" ::"r"(a), "r"(par) : "memory");
}
__device__ __forceinline__ void mbar_wait_fast(uint32_t a, uint32_t par) { mbar_wait(a, par); }
__device__ __forceinline__ void mbar_wait_checked(uint32_t a, uint32_t par) {
  asm volatile("{\n.reg .pred p;\n.reg .u32 n;\nmov.u32 n, 0;\n"
               "LW:\nmbarrier.try_wait.parity.shared::cta.b64 p, [%0], %1;\n@p bra LD;\n"
               "nanosleep.u32 1000;\nadd.u32 n, n, 1;\nsetp.lt.u32 p, n, %2;\n@p bra LW;\ntrap;\nLD:\n}\n" ::"r"(a), "r"(par), "n"(SPIN_LIMIT) : "memory");
}
__device__ __forceinline__ void flag_wait(const unsigned* f, unsigned target) {
  asm volatile("{\n.reg .pred p;\n.reg .u32 n, v;\nmov.u32 n, 0;\n"
               "LW:\nld.acquire.gpu.global.u32 v, [%0];\nsub.u32 v, v, %1;\nsetp.ge.s32 p, v, 0;\n@p bra LD;\n"
               "add.u32 n, n, 1;\nsetp.lt.u32 p, n, %2;\n@p bra LW;\ntrap;\nLD:\n}\n" ::"l"(f), "r"(target), "n"(SPIN_LIMIT) : "memory");
}
__device__ __forceinline__ bool elect_one() {
  uint32_t r;
  asm volatile("{\n.reg .pred p;\nelect.sync _|p, 0xffffffff;\nselp.u32 %0, 1, 0, p;\n}\n" : "=r"(r));
  return r != 0;
}
__device__ __forceinline__ void flag_publish(unsigned* f) {
  asm volatile("fence.acq_rel.gpu;" ::: "memory");
  asm volatile("red.relaxed.gpu.global.add.u32 [%0], 1;" ::"l"(f) : "memory");
}
__device__ __forceinline__ void bar_sync(int id, int n) { asm volatile("bar.sync %0, %1;" ::"r"(id), "r"(n) : "memory"); }
__device__ __forceinline__ void bar_arrive(int id, int n) { asm volatile("bar.arrive %0, %1;" ::"r"(id), "r"(n) : "memory"); }
__device__ __forceinline__ uint32_t peer_addr(uint32_t a, uint32_t rank) { uint32_t r; asm("mapa.shared::cluster.u32 %0, %1, %2;" : "=r"(r) : "r"(a), "r"(rank)); return r; }
__device__ __forceinline__ void mbar_arrive_remote(uint32_t a) { asm volatile("mbarrier.arrive.shared::cluster.b64 _, [%0];" ::"r"(a) : "memory"); }
__device__ __forceinline__ void st_async4(uint32_t a, float x, float y, float z, float w, uint32_t bar) {
  asm volatile("st.async.weak.shared::cluster.mbarrier::complete_tx::bytes.v4.f32 [%0], {%1, %2, %3, %4}, [%5];" ::"r"(a), "f"(x), "f"(y), "f"(z), "f"(w), "r"(bar) : "memory");
}
__device__ __forceinline__ void fence_async_smem() { asm volatile("fence.proxy.async.shared::cta;" ::: "memory"); }
__device__ __forceinline__ void fence_async_all() { asm volatile("fence.proxy.async.global;" ::: "memory"); }
__device__ __forceinline__ void wg_fence() { asm volatile("wgmma.fence.sync.aligned;" ::: "memory"); }
__device__ __forceinline__ void wg_commit() { asm volatile("wgmma.commit_group.sync.aligned;" ::: "memory"); }
template <int N> __device__ __forceinline__ void wg_wait() { asm volatile("wgmma.wait_group.sync.aligned %0;" ::"n"(N) : "memory"); }

__device__ __forceinline__ void bulk_g2s(uint32_t dst, const void* src, uint32_t bytes, uint32_t bar) {
  asm volatile("cp.async.bulk.shared::cluster.global.mbarrier::complete_tx::bytes [%0], [%1], %2, [%3];" ::"r"(dst), "l"(src), "r"(bytes), "r"(bar) : "memory");
}
__device__ __forceinline__ void tma_2d(uint32_t dst, const CUtensorMap* m, int c0, int c1, uint32_t bar) {
  asm volatile("cp.async.bulk.tensor.2d.shared::cluster.global.mbarrier::complete_tx::bytes [%0], [%1, {%2, %3}], [%4];"
               ::"r"(dst), "l"(m), "r"(c0), "r"(c1), "r"(bar) : "memory");
}
__device__ __forceinline__ void tma_4d(uint32_t dst, const CUtensorMap* m, int c0, int c1, int c2, int c3, uint32_t bar) {
  asm volatile("cp.async.bulk.tensor.4d.shared::cluster.global.mbarrier::complete_tx::bytes [%0], [%1, {%2, %3, %4, %5}], [%6];"
               ::"r"(dst), "l"(m), "r"(c0), "r"(c1), "r"(c2), "r"(c3), "r"(bar) : "memory");
}
__device__ __forceinline__ void tma_2d_mc(uint32_t dst, const CUtensorMap* m, int c0, int c1, uint32_t bar) {
  asm volatile("cp.async.bulk.tensor.2d.shared::cluster.global.mbarrier::complete_tx::bytes.multicast::cluster [%0], [%1, {%2, %3}], [%4], %5;"
               ::"r"(dst), "l"(m), "r"(c0), "r"(c1), "r"(bar), "h"((uint16_t)3) : "memory");
}
__device__ __forceinline__ void tma_3d(uint32_t dst, const CUtensorMap* m, int c0, int c1, int c2, uint32_t bar) {
  asm volatile("cp.async.bulk.tensor.3d.shared::cluster.global.mbarrier::complete_tx::bytes [%0], [%1, {%2, %3, %4}], [%5];"
               ::"r"(dst), "l"(m), "r"(c0), "r"(c1), "r"(c2), "r"(bar) : "memory");
}
__device__ __forceinline__ void tma_5d(uint32_t dst, const CUtensorMap* m, int c0, int c1, int c2, int c3, int c4, uint32_t bar) {
  asm volatile("cp.async.bulk.tensor.5d.shared::cluster.global.mbarrier::complete_tx::bytes [%0], [%1, {%2, %3, %4, %5, %6}], [%7];"
               ::"r"(dst), "l"(m), "r"(c0), "r"(c1), "r"(c2), "r"(c3), "r"(c4), "r"(bar) : "memory");
}
__device__ __forceinline__ void tmap_prefetch(const CUtensorMap* m) { asm volatile("prefetch.tensormap [%0];" ::"l"(m) : "memory"); }
__device__ __forceinline__ void l2_prefetch(const void* p, uint32_t bytes) { asm volatile("cp.async.bulk.prefetch.L2.global [%0], %1;" ::"l"(p), "r"(bytes) : "memory"); }

template <class T> __device__ __forceinline__ T* sptr(uint32_t a) { return reinterpret_cast<T*>(__cvta_shared_to_generic(a)); }
__device__ __forceinline__ uint32_t lds32(uint32_t a) { return *sptr<const uint32_t>(a); }
__device__ __forceinline__ float ldsf(uint32_t a) { return *sptr<const float>(a); }
__device__ __forceinline__ float2 ldsf2(uint32_t a) { return *sptr<const float2>(a); }
__device__ __forceinline__ uint4 lds128(uint32_t a) { return *sptr<const uint4>(a); }
__device__ __forceinline__ void sts32(uint32_t a, uint32_t v) { *sptr<uint32_t>(a) = v; }
__device__ __forceinline__ void stsf(uint32_t a, float v) { *sptr<float>(a) = v; }
__device__ __forceinline__ void stsf2(uint32_t a, float x, float y) { *sptr<float2>(a) = make_float2(x, y); }
__device__ __forceinline__ void sts128(uint32_t a, uint4 v) { *sptr<uint4>(a) = v; }
__device__ __forceinline__ void ldsm4t(uint32_t a, uint32_t& r0, uint32_t& r1, uint32_t& r2, uint32_t& r3) {
  asm volatile("ldmatrix.sync.aligned.m8n8.x4.trans.shared.b16 {%0, %1, %2, %3}, [%4];" : "=r"(r0), "=r"(r1), "=r"(r2), "=r"(r3) : "r"(a) : "memory");
}
__device__ __forceinline__ void red_add4(float* p, uint4 v) {
  asm volatile("red.relaxed.gpu.global.add.v4.f32 [%0], {%1, %2, %3, %4};" ::"l"(p), "f"(__uint_as_float(v.x)), "f"(__uint_as_float(v.y)),
               "f"(__uint_as_float(v.z)), "f"(__uint_as_float(v.w)) : "memory");
}
__device__ __forceinline__ void ldsm4(uint32_t a, uint32_t& r0, uint32_t& r1, uint32_t& r2, uint32_t& r3) {
  asm volatile("ldmatrix.sync.aligned.m8n8.x4.shared.b16 {%0, %1, %2, %3}, [%4];" : "=r"(r0), "=r"(r1), "=r"(r2), "=r"(r3) : "r"(a) : "memory");
}
__device__ __forceinline__ void stsm4(uint32_t a, uint32_t r0, uint32_t r1, uint32_t r2, uint32_t r3) {
  asm volatile("stmatrix.sync.aligned.m8n8.x4.shared.b16 [%0], {%1, %2, %3, %4};" ::"r"(a), "r"(r0), "r"(r1), "r"(r2), "r"(r3) : "memory");
}
__device__ __forceinline__ void stsm4t(uint32_t a, uint32_t r0, uint32_t r1, uint32_t r2, uint32_t r3) {
  asm volatile("stmatrix.sync.aligned.m8n8.x4.trans.shared.b16 [%0], {%1, %2, %3, %4};" ::"r"(a), "r"(r0), "r"(r1), "r"(r2), "r"(r3) : "memory");
}
__device__ __forceinline__ uint4 ldg128_cg(const void* p) { uint4 v; asm volatile("ld.global.cg.v4.b32 {%0, %1, %2, %3}, [%4];" : "=r"(v.x), "=r"(v.y), "=r"(v.z), "=r"(v.w) : "l"(p) : "memory"); return v; }
__device__ __forceinline__ uint4 ldg128_nc(const void* p) { uint4 v; asm volatile("ld.global.nc.v4.b32 {%0, %1, %2, %3}, [%4];" : "=r"(v.x), "=r"(v.y), "=r"(v.z), "=r"(v.w) : "l"(p)); return v; }

__device__ __forceinline__ float bf_lo(uint32_t v) { return __uint_as_float(v << 16); }
__device__ __forceinline__ float bf_hi(uint32_t v) { return __uint_as_float(v & 0xffff0000u); }
__device__ __forceinline__ uint32_t pack_bf(float lo, float hi) { uint32_t r; asm("cvt.rn.bf16x2.f32 %0, %1, %2;" : "=r"(r) : "f"(hi), "f"(lo)); return r; }
__device__ __forceinline__ uint32_t pack_h(float lo, float hi) { uint32_t r; asm("cvt.rn.f16x2.f32 %0, %1, %2;" : "=r"(r) : "f"(hi), "f"(lo)); return r; }
__device__ __forceinline__ uint32_t bf2_add(uint32_t a, uint32_t b) { uint32_t r; asm("add.rn.bf16x2 %0, %1, %2;" : "=r"(r) : "r"(a), "r"(b)); return r; }
__device__ __forceinline__ uint32_t bf2_sub(uint32_t a, uint32_t b) { uint32_t r; asm("sub.rn.bf16x2 %0, %1, %2;" : "=r"(r) : "r"(a), "r"(b)); return r; }
__device__ __forceinline__ float bf_round(float x) { return bf_lo(pack_bf(x, 0.f)); }
__device__ __forceinline__ float2 unpack_h(uint32_t v) { return __half22float2(*reinterpret_cast<const __half2*>(&v)); }
__device__ __forceinline__ float ex2f(float x) { float y; asm("ex2.approx.ftz.f32 %0, %1;" : "=f"(y) : "f"(x)); return y; }
__device__ __forceinline__ float rcpf(float x) { float y; asm("rcp.approx.ftz.f32 %0, %1;" : "=f"(y) : "f"(x)); return y; }
__device__ __forceinline__ float bf2f(bf16 v) { return __bfloat162float(v); }

template <int N> __device__ __forceinline__ void pin_regs(float (&a)[N]) {
#pragma unroll
  for (int i = 0; i < N; i++) asm volatile("" : "+f"(a[i])::"memory");
}

__device__ __forceinline__ uint32_t g2_stage_off(uint32_t st) { return st < 3 ? SM_WR + st * G2_STAGE : (st - 3) * G2_STAGE; }
__device__ __forceinline__ uint32_t desc_lo(uint32_t addr, uint32_t lbo) { return ((addr & 0x3FFFF) >> 4) | ((lbo >> 4) << 16); }

__device__ __forceinline__ float2 ln_finalize(float sum, float sq) {
  const float mean = sum * (1.0f / DM);
  const float var = fmaxf(fmaf(-mean, mean, sq * (1.0f / DM)), 0.f);
  const float ve = bf_round(bf_round(var) + 1e-5f);
  float s;
  asm("sqrt.approx.ftz.f32 %0, %1;" : "=f"(s) : "f"(ve));
  return make_float2(bf_round(mean), rcpf(bf_round(s)));
}

__device__ __forceinline__ void wg_g1_n128(float (&d)[64], uint32_t da, uint32_t db, int scale_d) {
  asm volatile("{\n.reg .pred p;\n.reg .b64 da, db;\n.reg .b32 ha, hb;\nsetp.ne.b32 p, %66, 0;\n"
    "mov.b32 ha, 1073741888;\nmov.b32 hb, 1073741888;\nmov.b64 da, {%64, ha};\nmov.b64 db, {%65, hb};\n"
    "wgmma.mma_async.sync.aligned.m64n128k16.f32.bf16.bf16 "
    "{%0, %1, %2, %3, %4, %5, %6, %7, %8, %9, %10, %11, %12, %13, %14, %15, %16, %17, %18, %19, %20, %21, %22, %23, %24, %25, %26, %27, %28, %29, %30, %31, %32, %33, %34, %35, %36, %37, %38, %39, %40, %41, %42, %43, %44, %45, %46, %47, %48, %49, %50, %51, %52, %53, %54, %55, %56, %57, %58, %59, %60, %61, %62, %63}, "
    "da, db, p, 1, 1, 1, 1;\n}\n"
    : "+f"(d[0]), "+f"(d[1]), "+f"(d[2]), "+f"(d[3]), "+f"(d[4]), "+f"(d[5]), "+f"(d[6]), "+f"(d[7]), "+f"(d[8]), "+f"(d[9]), "+f"(d[10]), "+f"(d[11]), "+f"(d[12]), "+f"(d[13]), "+f"(d[14]), "+f"(d[15]), "+f"(d[16]), "+f"(d[17]), "+f"(d[18]), "+f"(d[19]), "+f"(d[20]), "+f"(d[21]), "+f"(d[22]), "+f"(d[23]), "+f"(d[24]), "+f"(d[25]), "+f"(d[26]), "+f"(d[27]), "+f"(d[28]), "+f"(d[29]), "+f"(d[30]), "+f"(d[31]), "+f"(d[32]), "+f"(d[33]), "+f"(d[34]), "+f"(d[35]), "+f"(d[36]), "+f"(d[37]), "+f"(d[38]), "+f"(d[39]), "+f"(d[40]), "+f"(d[41]), "+f"(d[42]), "+f"(d[43]), "+f"(d[44]), "+f"(d[45]), "+f"(d[46]), "+f"(d[47]), "+f"(d[48]), "+f"(d[49]), "+f"(d[50]), "+f"(d[51]), "+f"(d[52]), "+f"(d[53]), "+f"(d[54]), "+f"(d[55]), "+f"(d[56]), "+f"(d[57]), "+f"(d[58]), "+f"(d[59]), "+f"(d[60]), "+f"(d[61]), "+f"(d[62]), "+f"(d[63])
    : "r"(da), "r"(db), "r"(scale_d));
}
__device__ __forceinline__ void wg_g1_n112(float (&d)[64], uint32_t da, uint32_t db, int scale_d) {
  asm volatile("{\n.reg .pred p;\n.reg .b64 da, db;\n.reg .b32 ha, hb;\nsetp.ne.b32 p, %58, 0;\n"
    "mov.b32 ha, 1073741888;\nmov.b32 hb, 1073741888;\nmov.b64 da, {%56, ha};\nmov.b64 db, {%57, hb};\n"
    "wgmma.mma_async.sync.aligned.m64n112k16.f32.bf16.bf16 "
    "{%0, %1, %2, %3, %4, %5, %6, %7, %8, %9, %10, %11, %12, %13, %14, %15, %16, %17, %18, %19, %20, %21, %22, %23, %24, %25, %26, %27, %28, %29, %30, %31, %32, %33, %34, %35, %36, %37, %38, %39, %40, %41, %42, %43, %44, %45, %46, %47, %48, %49, %50, %51, %52, %53, %54, %55}, "
    "da, db, p, 1, 1, 1, 1;\n}\n"
    : "+f"(d[0]), "+f"(d[1]), "+f"(d[2]), "+f"(d[3]), "+f"(d[4]), "+f"(d[5]), "+f"(d[6]), "+f"(d[7]), "+f"(d[8]), "+f"(d[9]), "+f"(d[10]), "+f"(d[11]), "+f"(d[12]), "+f"(d[13]), "+f"(d[14]), "+f"(d[15]), "+f"(d[16]), "+f"(d[17]), "+f"(d[18]), "+f"(d[19]), "+f"(d[20]), "+f"(d[21]), "+f"(d[22]), "+f"(d[23]), "+f"(d[24]), "+f"(d[25]), "+f"(d[26]), "+f"(d[27]), "+f"(d[28]), "+f"(d[29]), "+f"(d[30]), "+f"(d[31]), "+f"(d[32]), "+f"(d[33]), "+f"(d[34]), "+f"(d[35]), "+f"(d[36]), "+f"(d[37]), "+f"(d[38]), "+f"(d[39]), "+f"(d[40]), "+f"(d[41]), "+f"(d[42]), "+f"(d[43]), "+f"(d[44]), "+f"(d[45]), "+f"(d[46]), "+f"(d[47]), "+f"(d[48]), "+f"(d[49]), "+f"(d[50]), "+f"(d[51]), "+f"(d[52]), "+f"(d[53]), "+f"(d[54]), "+f"(d[55])
    : "r"(da), "r"(db), "r"(scale_d));
}
__device__ __forceinline__ void wg_g2_n128(float (&d)[64], uint32_t da, uint32_t db, int scale_d) {
  asm volatile("{\n.reg .pred p;\n.reg .b64 da, db;\n.reg .b32 ha, hb;\nsetp.ne.b32 p, %66, 0;\n"
    "mov.b32 ha, 1073741888;\nmov.b32 hb, 8;\nmov.b64 da, {%64, ha};\nmov.b64 db, {%65, hb};\n"
    "wgmma.mma_async.sync.aligned.m64n128k16.f32.bf16.bf16 "
    "{%0, %1, %2, %3, %4, %5, %6, %7, %8, %9, %10, %11, %12, %13, %14, %15, %16, %17, %18, %19, %20, %21, %22, %23, %24, %25, %26, %27, %28, %29, %30, %31, %32, %33, %34, %35, %36, %37, %38, %39, %40, %41, %42, %43, %44, %45, %46, %47, %48, %49, %50, %51, %52, %53, %54, %55, %56, %57, %58, %59, %60, %61, %62, %63}, "
    "da, db, p, 1, 1, 1, 0;\n}\n"
    : "+f"(d[0]), "+f"(d[1]), "+f"(d[2]), "+f"(d[3]), "+f"(d[4]), "+f"(d[5]), "+f"(d[6]), "+f"(d[7]), "+f"(d[8]), "+f"(d[9]), "+f"(d[10]), "+f"(d[11]), "+f"(d[12]), "+f"(d[13]), "+f"(d[14]), "+f"(d[15]), "+f"(d[16]), "+f"(d[17]), "+f"(d[18]), "+f"(d[19]), "+f"(d[20]), "+f"(d[21]), "+f"(d[22]), "+f"(d[23]), "+f"(d[24]), "+f"(d[25]), "+f"(d[26]), "+f"(d[27]), "+f"(d[28]), "+f"(d[29]), "+f"(d[30]), "+f"(d[31]), "+f"(d[32]), "+f"(d[33]), "+f"(d[34]), "+f"(d[35]), "+f"(d[36]), "+f"(d[37]), "+f"(d[38]), "+f"(d[39]), "+f"(d[40]), "+f"(d[41]), "+f"(d[42]), "+f"(d[43]), "+f"(d[44]), "+f"(d[45]), "+f"(d[46]), "+f"(d[47]), "+f"(d[48]), "+f"(d[49]), "+f"(d[50]), "+f"(d[51]), "+f"(d[52]), "+f"(d[53]), "+f"(d[54]), "+f"(d[55]), "+f"(d[56]), "+f"(d[57]), "+f"(d[58]), "+f"(d[59]), "+f"(d[60]), "+f"(d[61]), "+f"(d[62]), "+f"(d[63])
    : "r"(da), "r"(db), "r"(scale_d));
}
__device__ __forceinline__ void wg_kg_n32(float (&d)[16], uint32_t da, uint32_t db, int scale_d) {
  asm volatile("{\n.reg .pred p;\n.reg .b64 da, db;\n.reg .b32 ha, hb;\nsetp.ne.b32 p, %18, 0;\n"
    "mov.b32 ha, 1073741888;\nmov.b32 hb, 1073741888;\nmov.b64 da, {%16, ha};\nmov.b64 db, {%17, hb};\n"
    "wgmma.mma_async.sync.aligned.m64n32k16.f32.f16.f16 "
    "{%0, %1, %2, %3, %4, %5, %6, %7, %8, %9, %10, %11, %12, %13, %14, %15}, "
    "da, db, p, 1, 1, 0, 0;\n}\n"
    : "+f"(d[0]), "+f"(d[1]), "+f"(d[2]), "+f"(d[3]), "+f"(d[4]), "+f"(d[5]), "+f"(d[6]), "+f"(d[7]), "+f"(d[8]), "+f"(d[9]), "+f"(d[10]), "+f"(d[11]), "+f"(d[12]), "+f"(d[13]), "+f"(d[14]), "+f"(d[15])
    : "r"(da), "r"(db), "r"(scale_d));
}
__device__ __forceinline__ void wg_cv_n64(float (&d)[32], uint32_t a0, uint32_t a1, uint32_t a2, uint32_t a3, uint32_t db, int scale_d) {
  asm volatile("{\n.reg .pred p;\n.reg .b64 db;\n.reg .b32 hb;\nsetp.ne.b32 p, %37, 0;\n"
    "mov.b32 hb, 2147483680;\nmov.b64 db, {%36, hb};\n"
    "wgmma.mma_async.sync.aligned.m64n64k16.f32.f16.f16 "
    "{%0, %1, %2, %3, %4, %5, %6, %7, %8, %9, %10, %11, %12, %13, %14, %15, %16, %17, %18, %19, %20, %21, %22, %23, %24, %25, %26, %27, %28, %29, %30, %31}, "
    "{%32, %33, %34, %35}, db, p, 1, 1, 0;\n}\n"
    : "+f"(d[0]), "+f"(d[1]), "+f"(d[2]), "+f"(d[3]), "+f"(d[4]), "+f"(d[5]), "+f"(d[6]), "+f"(d[7]), "+f"(d[8]), "+f"(d[9]), "+f"(d[10]), "+f"(d[11]), "+f"(d[12]), "+f"(d[13]), "+f"(d[14]), "+f"(d[15]), "+f"(d[16]), "+f"(d[17]), "+f"(d[18]), "+f"(d[19]), "+f"(d[20]), "+f"(d[21]), "+f"(d[22]), "+f"(d[23]), "+f"(d[24]), "+f"(d[25]), "+f"(d[26]), "+f"(d[27]), "+f"(d[28]), "+f"(d[29]), "+f"(d[30]), "+f"(d[31])
    : "r"(a0), "r"(a1), "r"(a2), "r"(a3), "r"(db), "r"(scale_d));
}
__device__ __forceinline__ void wg_cv_n56(float (&d)[28], uint32_t a0, uint32_t a1, uint32_t a2, uint32_t a3, uint32_t db, int scale_d) {
  asm volatile("{\n.reg .pred p;\n.reg .b64 db;\n.reg .b32 hb;\nsetp.ne.b32 p, %33, 0;\n"
    "mov.b32 hb, 2147483680;\nmov.b64 db, {%32, hb};\n"
    "wgmma.mma_async.sync.aligned.m64n56k16.f32.f16.f16 "
    "{%0, %1, %2, %3, %4, %5, %6, %7, %8, %9, %10, %11, %12, %13, %14, %15, %16, %17, %18, %19, %20, %21, %22, %23, %24, %25, %26, %27}, "
    "{%28, %29, %30, %31}, db, p, 1, 1, 0;\n}\n"
    : "+f"(d[0]), "+f"(d[1]), "+f"(d[2]), "+f"(d[3]), "+f"(d[4]), "+f"(d[5]), "+f"(d[6]), "+f"(d[7]), "+f"(d[8]), "+f"(d[9]), "+f"(d[10]), "+f"(d[11]), "+f"(d[12]), "+f"(d[13]), "+f"(d[14]), "+f"(d[15]), "+f"(d[16]), "+f"(d[17]), "+f"(d[18]), "+f"(d[19]), "+f"(d[20]), "+f"(d[21]), "+f"(d[22]), "+f"(d[23]), "+f"(d[24]), "+f"(d[25]), "+f"(d[26]), "+f"(d[27])
    : "r"(a0), "r"(a1), "r"(a2), "r"(a3), "r"(db), "r"(scale_d));
}
__device__ __forceinline__ void wg_cv_n40(float (&d)[20], uint32_t a0, uint32_t a1, uint32_t a2, uint32_t a3, uint32_t db, int scale_d) {
  asm volatile("{\n.reg .pred p;\n.reg .b64 db;\n.reg .b32 hb;\nsetp.ne.b32 p, %25, 0;\n"
    "mov.b32 hb, 2147483680;\nmov.b64 db, {%24, hb};\n"
    "wgmma.mma_async.sync.aligned.m64n40k16.f32.f16.f16 "
    "{%0, %1, %2, %3, %4, %5, %6, %7, %8, %9, %10, %11, %12, %13, %14, %15, %16, %17, %18, %19}, "
    "{%20, %21, %22, %23}, db, p, 1, 1, 0;\n}\n"
    : "+f"(d[0]), "+f"(d[1]), "+f"(d[2]), "+f"(d[3]), "+f"(d[4]), "+f"(d[5]), "+f"(d[6]), "+f"(d[7]), "+f"(d[8]), "+f"(d[9]), "+f"(d[10]), "+f"(d[11]), "+f"(d[12]), "+f"(d[13]), "+f"(d[14]), "+f"(d[15]), "+f"(d[16]), "+f"(d[17]), "+f"(d[18]), "+f"(d[19])
    : "r"(a0), "r"(a1), "r"(a2), "r"(a3), "r"(db), "r"(scale_d));
}
__device__ __forceinline__ void wg_cv_n16t(float (&d)[8], uint32_t a0, uint32_t a1, uint32_t a2, uint32_t a3, uint32_t db, int scale_d) {
  asm volatile("{\n.reg .pred p;\n.reg .b64 db;\n.reg .b32 hb;\nsetp.ne.b32 p, %13, 0;\n"
    "mov.b32 hb, 3221225488;\nmov.b64 db, {%12, hb};\n"
    "wgmma.mma_async.sync.aligned.m64n16k16.f32.f16.f16 "
    "{%0, %1, %2, %3, %4, %5, %6, %7}, "
    "{%8, %9, %10, %11}, db, p, 1, 1, 1;\n}\n"
    : "+f"(d[0]), "+f"(d[1]), "+f"(d[2]), "+f"(d[3]), "+f"(d[4]), "+f"(d[5]), "+f"(d[6]), "+f"(d[7])
    : "r"(a0), "r"(a1), "r"(a2), "r"(a3), "r"(db), "r"(scale_d));
}

__device__ __forceinline__ float2 cmul(float2 a, float2 b) {
  return make_float2(fmaf(a.x, b.x, -a.y * b.y), fmaf(a.x, b.y, a.y * b.x));
}
__device__ __forceinline__ float2 cexp_p(float ar, float ai, float p) {
  float xr = ar * p, xi = ai * p;
  float mag = ex2f(xr * 1.4426950408889634f);
  float k = rintf(xi * 0.15915494309189535f);
  float r = fmaf(-k, 6.2831854820251465f, xi);
  r = fmaf(-k, -1.7484555314695172e-07f, r);
  float s, c;
  __sincosf(r, &s, &c);
  return make_float2(mag * c, mag * s);
}
__device__ __forceinline__ int pos_index(int j) {
  int b = (int)(pack_bf((float)j, 0.f) & 0xffffu) - 17024;
  return j < 128 ? j : b;
}

struct KParam { float logA, aim, cre, cim, logdt; };

__device__ __forceinline__ void kgen(uint32_t sb, int w, int wp, int lane, const KParam (&kp)[2], float (&kinv)[2]) {
  const int t = wp * 32 + lane;
  float ar[2], ai[2];
  float2 C[2];
  const uint32_t mxa = sb + SM_MISC + 12288 + w * 32;
#pragma unroll
  for (int v = 0; v < 2; v++) {
    const float dt = bf_round(expf(kp[v].logdt));
    const float lar = -bf_round(expf(kp[v].logA));
    ar[v] = lar * dt; ai[v] = kp[v].aim * dt;
    C[v] = make_float2(kp[v].cre * dt, kp[v].cim * dt);
    float mx = fmaxf(fabsf(C[v].x), fabsf(C[v].y));
#pragma unroll
    for (int o = 16; o; o >>= 1) mx = fmaxf(mx, __shfl_xor_sync(0xffffffffu, mx, o));
    if (lane == 0) stsf(mxa + v * 16 + wp * 4, mx);
  }
  bar_sync(1 + w, 128);
#pragma unroll
  for (int v = 0; v < 2; v++) {
    const uint4 m4 = lds128(mxa + v * 16);
    const float mx = fmaxf(fmaxf(__uint_as_float(m4.x), __uint_as_float(m4.y)), fmaxf(__uint_as_float(m4.z), __uint_as_float(m4.w)));
    int e = (__float_as_uint(mx) >> 23) & 255;
    e = min(max(e, 4), 254);
    const float scale2 = __uint_as_float((uint32_t)(258 - e) << 23);
    kinv[v] = __uint_as_float((uint32_t)(e - 3) << 23);
    C[v].x *= scale2; C[v].y *= scale2;
  }
  const uint32_t ga = sb + KG_A + w * 28672 + wp * 3072 + lane * 4;
  const uint32_t fa = sb + KG_B + w * 28672 + wp * 4096 + lane * 4;
  auto putG = [&](int v, int h, float2 g) { sts32(((ga + v * 57344) ^ ((h & 7) << 4)) + h * 128, pack_h(g.x, -g.y)); };
  float2 E8[2];
#pragma unroll
  for (int v = 0; v < 2; v++) {
    const float2 E1 = cexp_p(ar[v], ai[v], 1.f), E256 = cexp_p(ar[v], ai[v], 256.f);
    const float2 E2 = cmul(E1, E1), E4 = cmul(E2, E2), E512 = cmul(E256, E256), E1024 = cmul(E512, E512);
    E8[v] = cmul(E4, E4);
    {
      float2 g0 = C[v], g1 = cmul(C[v], E1);
      putG(v, 0, g0); putG(v, 1, g1);
#pragma unroll
      for (int h = 2; h < 8; h += 2) { g0 = cmul(g0, E2); g1 = cmul(g1, E2); putG(v, h, g0); putG(v, h + 1, g1); }
    }
    {
      const float2 g = cmul(C[v], E256), g4 = cmul(g, E4);
      putG(v, 8, g); putG(v, 9, cmul(g, E2)); putG(v, 10, g4); putG(v, 11, cmul(g4, E2));
    }
    {
      const float2 g = cmul(C[v], E512), g2 = cmul(g, E256);
      putG(v, 12, g); putG(v, 13, cmul(g, E4)); putG(v, 14, g2); putG(v, 15, cmul(g2, E4));
    }
    {
      const float2 g = cmul(C[v], E1024), g2 = cmul(g, E512);
      putG(v, 16, g); putG(v, 17, cmul(g, E256)); putG(v, 18, g2); putG(v, 19, cmul(g2, E256)); putG(v, 20, cmul(g, E1024));
    }
  }
  {
    float2 f[2][2], E16[2];
#pragma unroll
    for (int v = 0; v < 2; v++) { E16[v] = cmul(E8[v], E8[v]); f[v][0] = make_float2(1.f, 0.f); f[v][1] = E8[v]; }
#pragma unroll 2
    for (int o = 0; o < 32; o += 2) {
      const uint32_t a0 = (fa ^ ((o & 7) << 4)) + o * 128, a1 = (fa ^ (((o + 1) & 7) << 4)) + (o + 1) * 128;
#pragma unroll
      for (int v = 0; v < 2; v++) {
        sts32(a0 + v * 57344, pack_h(f[v][0].x, f[v][0].y));
        sts32(a1 + v * 57344, pack_h(f[v][1].x, f[v][1].y));
        f[v][0] = cmul(f[v][0], E16[v]); f[v][1] = cmul(f[v][1], E16[v]);
      }
    }
  }
  TS(37);
  fence_async_smem();
  bar_sync(1 + w, 128);
  float acc0[16], acc1[16];
#pragma unroll
  for (int i = 0; i < 16; i++) { acc0[i] = 0.f; acc1[i] = 0.f; }
  pin_regs(acc0); pin_regs(acc1);
  {
    const uint32_t da = desc_lo(sb + KG_A + w * 28672, 16), db = desc_lo(sb + KG_B + w * 28672, 16);
    wg_fence();
#pragma unroll 1
    for (int kb = 0; kb < 4; kb++) {
#pragma unroll
      for (int k = 0; k < 4; k++) {
        wg_kg_n32(acc0, da + kb * 192 + k * 2, db + kb * 256 + k * 2, (kb | k) != 0);
        wg_kg_n32(acc1, da + 3584 + kb * 192 + k * 2, db + 3584 + kb * 256 + k * 2, (kb | k) != 0);
      }
    }
    wg_commit();
    wg_wait<0>();
    pin_regs(acc0); pin_regs(acc1);
    if (lane == 0) mbar_arrive(sb + SM_BAR + 8 * B_KGDONE);
  }
  const uint32_t kt = sb + SM_MISC + w * 2592;
  {
    const int g = lane >> 2, c = lane & 3;
    if (wp == 0) {
      const int b2 = g < 4 ? 256 + g : 384 + 64 * ((g - 4) >> 1) + (g & 1), s2 = g < 4 ? 4 : 2;
      const uint32_t k0 = kt + (g + 16 * c) * 4, k1 = kt + (b2 + s2 * 2 * c) * 4;
#pragma unroll
      for (int nb = 0; nb < 4; nb++)
#pragma unroll
        for (int k = 0; k < 2; k++) {
          const int o = 8 * nb + k;
          stsf(k0 + 32 * o, acc0[4 * nb + k]); stsf(k0 + 32 * o + 5184, acc1[4 * nb + k]);
          stsf(k1 + s2 * 4 * o, acc0[4 * nb + 2 + k]); stsf(k1 + s2 * 4 * o + 5184, acc1[4 * nb + 2 + k]);
        }
    } else if (wp == 1) {
      if (g < 4) {
        const uint32_t k0 = kt + (512 + 32 * g + 2 * c) * 4;
#pragma unroll
        for (int nb = 0; nb < 4; nb++) { stsf2(k0 + 32 * nb, acc0[4 * nb], acc0[4 * nb + 1]); stsf2(k0 + 32 * nb + 5184, acc1[4 * nb], acc1[4 * nb + 1]); }
      } else if (g == 4 && c == 0) {
        stsf(kt + 640 * 4, acc0[0]); stsf(kt + 640 * 4 + 5184, acc1[0]);
      }
    }
  }
  bar_sync(1 + w, 128);
  const uint32_t pt = sb + SM_PT + w * (PTW * 4);
#pragma unroll 1
  for (int i = 0; i < 3; i++) {
    const int q = t + 128 * i;
    if (q < PAW / 4) {
      const int x0 = 4 * q - 65;
      float kv[2][5];
#pragma unroll
      for (int k = 0; k < 5; k++) {
        const int x = x0 + k;
        const bool ok = x >= 0 && x <= 1028;
        const uint32_t a = kt + (ok ? pos_index(x) : 0) * 4;
#pragma unroll
        for (int v = 0; v < 2; v++) { const float f = ldsf(a + v * 5184); kv[v][k] = ok ? f : 0.f; }
      }
#pragma unroll
      for (int v = 0; v < 2; v++)
        sts128(pt + v * (2 * PTW * 4) + q * 16, make_uint4(pack_h(kv[v][1], kv[v][0]), pack_h(kv[v][2], kv[v][1]), pack_h(kv[v][3], kv[v][2]), pack_h(kv[v][4], kv[v][3])));
    }
  }
  {
    const int z = t - 64;
#pragma unroll
    for (int v = 0; v < 2; v++) {
      const uint32_t k0 = kt + v * 5184 + 8 * max(z, 0);
      const float a = ldsf(k0 + 511 * 4), b = ldsf(k0 + 512 * 4), c = ldsf(k0 + 513 * 4), d = ldsf(k0 + 514 * 4);
      sts32(pt + v * (2 * PTW * 4) + (PAW + t) * 4, pack_h(z >= 0 ? d : 0.f, z >= 1 ? b : 0.f));
      sts32(pt + v * (2 * PTW * 4) + (PAW + 128 + t) * 4, pack_h(z >= 0 ? c : 0.f, z >= 1 ? a : 0.f));
    }
  }
  fence_async_smem();
  __syncwarp();
  if (lane == 0) mbar_arrive(sb + SM_BAR + 8 * B_PTDONE);
}

__device__ __forceinline__ void strip_transpose(uint32_t sb, int warp, int lane, int cta) {
  mbar_wait(sb + SM_BAR + 8 * B_STRIP, 0);
  TS(17);
  const int g = lane >> 2, c = lane & 3;
  const bool mine = (g >> 2) == (cta & 1);
  const uint32_t dst = sb + CV_XS + (g & 3) * 4096 + c * 4 + warp * 512;
  uint32_t r[8][4];
#pragma unroll
  for (int i = 0; i < 8; i++) ldsm4t(sb + SM_STRIP + ((warp * 8 + i) * 32 + lane) * 16, r[i][0], r[i][1], r[i][2], r[i][3]);
  if (mine) {
#pragma unroll
    for (int i = 0; i < 8; i++)
#pragma unroll
      for (int k = 0; k < 4; k++) sts32(dst + i * 64 + k * 16, r[i][k]);
  }
  fence_async_smem();
  __syncwarp();
  if (lane == 0) mbar_arrive(sb + SM_BAR + 8 * B_STRIPDONE);
}

__device__ __forceinline__ void load_mu2(uint32_t (&q)[16], uint32_t a) {
#pragma unroll
  for (int h = 0; h < 2; h++) {
    q[8 * h + 2] = lds32(a + h * 256); q[8 * h] = lds32(a + h * 256 + 32); q[8 * h + 1] = lds32(a + h * 256 + 64);
    q[8 * h + 4] = lds32(a + h * 256 + 96); q[8 * h + 5] = lds32(a + h * 256 + 128);
  }
}
__device__ __forceinline__ void fix_mu(uint32_t (&q)[16], int h) { q[8 * h + 3] = q[8 * h]; q[8 * h + 6] = q[8 * h + 1]; q[8 * h + 7] = q[8 * h + 4]; }
#define MU2_GROUP(FN, ACC, Q, DB, SC0)                        \
  do {                                                        \
    fix_mu(Q, 0); fix_mu(Q, 1);                               \
    wg_fence();                                               \
    FN(ACC, Q[0], Q[1], Q[2], Q[3], (DB) + 2, SC0);           \
    FN(ACC, Q[4], Q[5], Q[6], Q[7], (DB), 1);                 \
    FN(ACC, Q[8], Q[9], Q[10], Q[11], (DB) - 8 + 2, 1);       \
    FN(ACC, Q[12], Q[13], Q[14], Q[15], (DB) - 8, 1);         \
    wg_commit();                                              \
  } while (0)
__device__ __forceinline__ void load_far(uint32_t (&q)[16], uint32_t a) {
  q[2] = lds32(a);
#pragma unroll
  for (int k = 0; k < 4; k++) { q[4 * k] = lds32(a + (2 * k + 1) * 32); q[4 * k + 1] = lds32(a + (2 * k + 2) * 32); }
}
#define FAR_GROUP(ACC, Q, DB, SC0)                                                        \
  do {                                                                                    \
    _Pragma("unroll") for (int k = 0; k < 4; k++) { Q[4 * k + 3] = Q[4 * k]; if (k) Q[4 * k + 2] = Q[4 * k - 3]; } \
    wg_fence();                                                                           \
    wg_cv_n16t(ACC, Q[0], Q[1], Q[2], Q[3], (DB) + 96, SC0);                              \
    wg_cv_n16t(ACC, Q[4], Q[5], Q[6], Q[7], (DB) + 64, 1);                                \
    wg_cv_n16t(ACC, Q[8], Q[9], Q[10], Q[11], (DB) + 32, 1);                              \
    wg_cv_n16t(ACC, Q[12], Q[13], Q[14], Q[15], (DB), 1);                                 \
    wg_commit();                                                                          \
  } while (0)

__device__ __forceinline__ uint32_t u_chunk(uint32_t base, int q) {
  const int qq = q + 64, row = qq >> 2;
  return base + row * 64 + (((qq & 3) ^ ((row >> 1) & 3)) << 4);
}

__device__ __forceinline__ void conv_phase(const Params& p, uint32_t sb, int layer, int w, int wp, int lane, int cta,
                                           float kinvA, float kinvB) {
  const int t = wp * 32 + lane, T = w * 128 + t;
  const uint32_t bar = sb + SM_BAR;
  if (layer == 0) bar_sync(4, 256);
  sts128(sb + CV_U + (w + 2 * (t >> 6)) * 5120 + (t & 63) * 16, make_uint4(0, 0, 0, 0));
  mbar_wait(bar + 8 * B_XSFULL, layer);
  TS(3 + 20 * layer);
  {
    uint4 v[4];
#pragma unroll
    for (int i = 0; i < 4; i++) v[i] = lds128(sb + CV_B97 + T * 64 + i * 16);
    const uint32_t sa = sb + SM_STAT + (T >> 1) * 16 + (T & 1) * 8192;
#pragma unroll
    for (int i = 0; i < 4; i++) {
      const float2 a = ln_finalize(__uint_as_float(v[i].x), __uint_as_float(v[i].y));
      const float2 b = ln_finalize(__uint_as_float(v[i].z), __uint_as_float(v[i].w));
      sts128(sa + i * 2048, make_uint4(__byte_perm(__float_as_uint(a.x), __float_as_uint(b.x), 0x7632), __float_as_uint(a.y), __float_as_uint(b.y), 0));
    }
    bar_sync(4, 256);
  }
  {
    uint4 st[8], x[4];
#pragma unroll
    for (int i = 0; i < 8; i++) st[i] = lds128(sb + SM_STAT + t * 16 + i * 2048);
#pragma unroll
    for (int i = 0; i < 4; i++) x[i] = lds128(sb + CV_XS + (w + 2 * (i >> 1)) * 4096 + t * 32 + (i & 1) * 16);
#pragma unroll
    for (int i = 0; i < 4; i++) {
      const uint32_t xx[4] = {x[i].x, x[i].y, x[i].z, x[i].w};
      uint32_t hh[4];
#pragma unroll
      for (int k = 0; k < 4; k++) {
        const uint4 s4 = st[4 * (i & 1) + k];
        const uint32_t dd = bf2_sub(xx[k], s4.x);
        hh[k] = pack_h(bf_lo(dd) * __uint_as_float(s4.y), bf_hi(dd) * __uint_as_float(s4.z));
      }
      sts128(u_chunk(sb + CV_U + (w + 2 * (i >> 1)) * 5120, 2 * t + (i & 1)), make_uint4(hh[0], hh[1], hh[2], hh[3]));
    }
  }
  fence_async_smem();
  bar_sync(4, 256);
  if (w == 1) {
#pragma unroll 1
    for (int h2 = 0; h2 < 2; h2++) {
      uint4 x[8];
#pragma unroll
      for (int k = 0; k < 8; k++) x[k] = lds128(u_chunk(sb + CV_U + (2 * h2 + (k >> 2)) * 5120, t - 3 + (k & 3)));
#pragma unroll
      for (int v = 0; v < 2; v++) {
        float u[32];
#pragma unroll
        for (int k = 0; k < 4; k++) {
          float2 f;
          f = unpack_h(x[4 * v + k].x); u[8 * k] = f.x; u[8 * k + 1] = f.y;
          f = unpack_h(x[4 * v + k].y); u[8 * k + 2] = f.x; u[8 * k + 3] = f.y;
          f = unpack_h(x[4 * v + k].z); u[8 * k + 4] = f.x; u[8 * k + 5] = f.y;
          f = unpack_h(x[4 * v + k].w); u[8 * k + 6] = f.x; u[8 * k + 7] = f.y;
        }
        float s9[8], s7[8];
        s9[0] = ((u[4] + u[5]) + (u[6] + u[7])) + ((u[8] + u[9]) + (u[10] + u[11])) + u[12];
        s9[4] = ((u[8] + u[9]) + (u[10] + u[11])) + ((u[12] + u[13]) + (u[14] + u[15])) + u[16];
        s7[0] = ((u[13] + u[14]) + (u[15] + u[16])) + ((u[17] + u[18]) + u[19]);
        s7[4] = ((u[17] + u[18]) + (u[19] + u[20])) + ((u[21] + u[22]) + u[23]);
#pragma unroll
        for (int j = 1; j < 4; j++) {
          s9[j] = s9[j - 1] + (u[j + 12] - u[j + 3]); s9[j + 4] = s9[j + 3] + (u[j + 16] - u[j + 7]);
          s7[j] = s7[j - 1] + (u[j + 19] - u[j + 12]); s7[j + 4] = s7[j + 3] + (u[j + 23] - u[j + 16]);
        }
        const uint32_t off = (uint32_t)(t * 16) ^ (((t >> 3) & 1) << 4);
        const uint32_t ba = sb + CV_B97 + (2 * h2 + v) * 4096 + off;
        sts128(ba, make_uint4(pack_h(s9[0], s9[1]), pack_h(s9[2], s9[3]), pack_h(s9[4], s9[5]), pack_h(s9[6], s9[7])));
        sts128(ba + 2048, make_uint4(pack_h(s7[0], s7[1]), pack_h(s7[2], s7[3]), pack_h(s7[4], s7[5]), pack_h(s7[6], s7[7])));
      }
    }
    fence_async_smem();
    __syncwarp();
    if (lane == 0) mbar_arrive(bar + 8 * B_B97);
  }
  if (layer != 0) mbar_wait(bar + 8 * B_PTFULL, 0);
  TS(4 + 20 * layer);

  const int g = lane >> 2, c = lane & 3;
  bf16* xout = p.sc->xT[layer == 0 ? 0 : 2];
  const uint32_t ex = sb + (w ? CV_E0 : CV_E1), y3 = ex + 8192;
  float ps[16], pq[16];
#pragma unroll
  for (int i = 0; i < 16; i++) { ps[i] = 0.f; pq[i] = 0.f; }
#pragma unroll 1
  for (int v = 0; v < 2; v++) {
    const int slot = w + 2 * v, ch = 4 * cta + slot;
    const float dsk = bf2f(p.Dsk[ch]);
    const uint32_t pa = sb + SM_PT + slot * (PTW * 4) + (64 + 16 * wp + g - 2 * c) * 4;
    const uint32_t ub = sb + CV_U + slot * 5120;
    const uint32_t du = desc_lo(ub + 16 * 64, 16);
    const uint32_t d9 = desc_lo(sb + CV_B97 + slot * 4096, 2048);
    float acc1[32], acc2[28], acc4[20], acc3[8];
#pragma unroll
    for (int i = 0; i < 32; i++) acc1[i] = 0.f;
#pragma unroll
    for (int i = 0; i < 28; i++) acc2[i] = 0.f;
#pragma unroll
    for (int i = 0; i < 20; i++) acc4[i] = 0.f;
#pragma unroll
    for (int i = 0; i < 8; i++) acc3[i] = 0.f;
    pin_regs(acc1); pin_regs(acc2); pin_regs(acc4); pin_regs(acc3);
    uint32_t qa[16], qb[16], qc[16];
    load_mu2(qa, pa - 3 * 32);
    load_mu2(qb, pa - 3 * 32 + 512);
    MU2_GROUP(wg_cv_n64, acc1, qa, du, 0);
    load_mu2(qc, pa - 3 * 32 + 1024);
    MU2_GROUP(wg_cv_n64, acc1, qb, du - 16, 1);
    wg_wait<1>();
    load_mu2(qa, pa - 3 * 32 + 1536);
    MU2_GROUP(wg_cv_n64, acc1, qc, du - 32, 1);
    wg_wait<1>();
    load_mu2(qb, pa - 3 * 32 + 2048);
    MU2_GROUP(wg_cv_n56, acc2, qa, du + 32 - 48, 0);
    wg_wait<1>();
    load_mu2(qc, pa - 3 * 32 + 2560);
    MU2_GROUP(wg_cv_n56, acc2, qb, du + 32 - 64, 1);
    wg_wait<1>();
    load_mu2(qa, pa - 3 * 32 + 3072);
    MU2_GROUP(wg_cv_n56, acc2, qc, du + 32 - 80, 1);
    wg_wait<1>();
    load_mu2(qb, pa - 3 * 32 + 3584);
    MU2_GROUP(wg_cv_n40, acc4, qa, du + 96 - 96, 0);
    wg_wait<1>();
    qc[2] = lds32(pa - 96 + 4096); qc[0] = lds32(pa - 64 + 4096); qc[1] = lds32(pa - 32 + 4096); qc[4] = lds32(pa + 4096); qc[5] = lds32(pa + 32 + 4096);
    MU2_GROUP(wg_cv_n40, acc4, qb, du + 96 - 112, 1);
    wg_wait<1>();
    load_far(qa, pa + PAW * 4 - 7 * 32);
    fix_mu(qc, 0);
    wg_fence();
    wg_cv_n40(acc4, qc[0], qc[1], qc[2], qc[3], du + 96 - 128 + 2, 1);
    wg_cv_n40(acc4, qc[4], qc[5], qc[6], qc[7], du + 96 - 128, 1);
    wg_commit();
    wg_wait<1>();
    load_far(qb, pa + (PAW + 128) * 4 - 7 * 32);
    mbar_wait(bar + 8 * B_B97, layer);
    FAR_GROUP(acc3, qa, d9, 0);
    FAR_GROUP(acc3, qb, d9 + (2048 >> 4), 1);
    wg_wait<0>();
    pin_regs(acc1); pin_regs(acc2); pin_regs(acc4); pin_regs(acc3);
    TS(5 + 2 * v + 20 * layer);

#pragma unroll
    for (int i = 0; i < 28; i++) acc1[4 + i] += acc2[i];
#pragma unroll
    for (int i = 0; i < 20; i++) acc1[12 + i] += acc4[i];
    if (wp >= 2) {
      const int src = (lane & ~3) | ((c + 3) & 3);
#pragma unroll
      for (int nb = 7; nb >= 0; nb--)
#pragma unroll
        for (int hh = 0; hh < 2; hh++) {
          const float cur1 = acc1[4 * nb + 2 * hh + 1];
          const float prev1 = nb ? acc1[4 * (nb - 1) + 2 * hh + 1] : 0.f;
          const float sh = __shfl_sync(0xffffffffu, c == 3 ? prev1 : cur1, src);
          acc1[4 * nb + 2 * hh + 1] = acc1[4 * nb + 2 * hh];
          acc1[4 * nb + 2 * hh] = sh;
        }
    }
    {
      const uint32_t ea = ex + (wp >> 1) * 4096 + (wp & 1) * 2048 + lane * 8;
#pragma unroll
      for (int j = 0; j < 8; j++) {
        const float a = wp >= 2 ? acc1[2 * j] : acc1[16 + 2 * j], b = wp >= 2 ? acc1[2 * j + 1] : acc1[16 + 2 * j + 1];
        stsf2(ea + j * 256, a, b);
      }
#pragma unroll
      for (int nb = 0; nb < 2; nb++)
#pragma unroll
        for (int hh = 0; hh < 2; hh++) {
          const int z = 16 * (16 * wp + g + 8 * hh) + 8 * nb + 2 * c;
          stsf2(y3 + (z ^ (((z >> 6) & 3) << 3)) * 4, acc3[4 * nb + 2 * hh], acc3[4 * nb + 2 * hh + 1]);
        }
    }
    bar_sync(1 + w, 128);
    {
      const float kinv = v ? kinvB : kinvA;
      const int hi = wp >> 1, wq = wp & 1;
      float yv[16];
      const uint32_t ea = ex + (hi ^ 1) * 4096 + wq * 2048 + lane * 8;
#pragma unroll
      for (int j = 0; j < 8; j++) {
        const float2 e = ldsf2(ea + j * 256);
        yv[2 * j] = e.x + (hi ? acc1[16 + 2 * j] : acc1[2 * j]);
        yv[2 * j + 1] = e.y + (hi ? acc1[16 + 2 * j + 1] : acc1[2 * j + 1]);
      }
      if (hi) {
#pragma unroll
        for (int j = 0; j < 16; j++) {
          const int z = 32 * (8 * (j >> 2) + 2 * c + (j & 1)) + 16 * wq + g + 8 * ((j >> 1) & 1);
          yv[j] += ldsf(y3 + (z ^ (((z >> 6) & 3) << 3)) * 4);
        }
      }
      const int mat = lane >> 3, ib = 32 * hi + (lane & 7) + 8 * (mat >> 1), r8 = 2 * wq + (mat & 1);
      uint32_t xr[8], ur[8];
#pragma unroll
      for (int h2 = 0; h2 < 2; h2++) {
        const int i = ib + 16 * h2;
        ldsm4t(sb + CV_XS + slot * 4096 + i * 64 + r8 * 16, xr[4 * h2], xr[4 * h2 + 1], xr[4 * h2 + 2], xr[4 * h2 + 3]);
        ldsm4t(u_chunk(ub, 4 * i + r8), ur[4 * h2], ur[4 * h2 + 1], ur[4 * h2 + 2], ur[4 * h2 + 3]);
      }
      uint32_t o[8];
#pragma unroll
      for (int j = 0; j < 8; j++) {
        const uint32_t yy = pack_bf(yv[2 * j] * kinv, yv[2 * j + 1] * kinv);
        const float2 uf = unpack_h(ur[j]);
        o[j] = bf2_add(xr[j], bf2_add(yy, pack_bf(uf.x * dsk, uf.y * dsk)));
      }
      const uint32_t ob = sb + CV_B97 + slot * 4096;
#pragma unroll
      for (int h2 = 0; h2 < 2; h2++) {
        const int i = ib + 16 * h2;
        stsm4t(ob + i * 64 + ((r8 ^ ((i >> 1) & 3)) << 4), o[4 * h2], o[4 * h2 + 1], o[4 * h2 + 2], o[4 * h2 + 3]);
      }
      bar_sync(1 + w, 128);
      const int i = t >> 1, c0 = (t & 1) * 2;
      const uint4 o0 = lds128(ob + i * 64 + ((c0 ^ ((i >> 1) & 3)) << 4)), o1 = lds128(ob + i * 64 + (((c0 + 1) ^ ((i >> 1) & 3)) << 4));
      uint4* dst = reinterpret_cast<uint4*>(xout + ch * SEQ + t * 16);
      dst[0] = o0;
      dst[1] = o1;
      __syncwarp();
      if (lane == 0) mbar_arrive(bar + 8 * (B_PUB + 2 * w + v));
      const uint32_t oo[8] = {o0.x, o0.y, o0.z, o0.w, o1.x, o1.y, o1.z, o1.w};
#pragma unroll
      for (int k = 0; k < 8; k++) {
        const float lo = bf_lo(oo[k]), hi2 = bf_hi(oo[k]);
        ps[2 * k] += lo; pq[2 * k] = fmaf(lo, lo, pq[2 * k]);
        ps[2 * k + 1] += hi2; pq[2 * k + 1] = fmaf(hi2, hi2, pq[2 * k + 1]);
      }
    }
    TS(6 + 2 * v + 20 * layer);
  }
  fence_async_smem();
  __syncwarp();
  if (lane == 0) mbar_arrive(bar + 8 * B_CONVDONE);
  const uint32_t sa = sb + SM_MISC + t * 128;
  if (w == 0) {
#pragma unroll
    for (int i = 0; i < 8; i++)
      sts128(sa + ((i ^ (t & 7)) << 4), make_uint4(__float_as_uint(ps[2 * i]), __float_as_uint(pq[2 * i]), __float_as_uint(ps[2 * i + 1]), __float_as_uint(pq[2 * i + 1])));
    bar_arrive(4, 256);
  } else {
    bar_sync(4, 256);
#pragma unroll
    for (int i = 0; i < 8; i++) {
      const uint32_t a = sa + ((i ^ (t & 7)) << 4);
      const uint4 o4 = lds128(a);
      sts128(a, make_uint4(__float_as_uint(ps[2 * i] + __uint_as_float(o4.x)), __float_as_uint(pq[2 * i] + __uint_as_float(o4.y)),
                           __float_as_uint(ps[2 * i + 1] + __uint_as_float(o4.z)), __float_as_uint(pq[2 * i + 1] + __uint_as_float(o4.w))));
    }
    fence_async_smem();
    __syncwarp();
    if (lane == 0) mbar_arrive(bar + 8 * B_STAGED);
  }
}

struct RowC { float a1[2], b1[2], r[2], rm[2]; };

struct CsV { float2 g[2], u[2]; };
__device__ __forceinline__ void g1_ldcs(CsV& c, uint32_t csa) {
#pragma unroll
  for (int j = 0; j < 2; j++) { c.g[j] = ldsf2(csa + j * 32); c.u[j] = ldsf2(csa + 176 * 4 + j * 32); }
}
template <int NB>
__device__ __forceinline__ void g1_slice(const float (&prv)[64], const CsV& c, const RowC& rc, uint32_t* hp) {
  float e[8], u[8];
#pragma unroll
  for (int i = 0; i < 8; i++) {
    const int j = i >> 2, hh = (i >> 1) & 1;
    e[i] = 1.f + ex2f(fmaf(prv[4 * NB + i], rc.a1[hh], ((i & 1) ? c.g[j].y : c.g[j].x) * rc.b1[hh]));
    u[i] = fmaf(prv[32 + 4 * NB + i], rc.r[hh], ((i & 1) ? c.u[j].y : c.u[j].x) * rc.rm[hh]);
  }
#pragma unroll
  for (int i = 0; i < 4; i++) hp[(NB + (i >> 1)) * 512 + (i & 1) * 32] = pack_bf(u[2 * i] * rcpf(e[2 * i]), u[2 * i + 1] * rcpf(e[2 * i + 1]));
}

struct Ring { uint32_t st, ph; };
template <int NV, bool XW>
__device__ __forceinline__ void g1_mma2(float (&acc)[64], uint32_t bar, uint32_t da, uint32_t dw, int kb, int sc0, bool rel, const Ring& rg, int layer) {
#pragma unroll
  for (int h = 0; h < 2; h++) {
    if (XW) mbar_wait(bar + 8 * B_XFULL + 8 * (kb + h), layer);
    mbar_wait(bar + 8 * B_WFULL + 8 * (rg.st + h), rg.ph);
    const uint32_t a = da + (kb + h) * 1024, b = dw + (rg.st + h) * 1024;
    wg_fence();
#pragma unroll
    for (int k = 0; k < 4; k++) {
      if (NV == 0) wg_g1_n128(acc, a + k * 128, b + k * 128, (h | k) ? 1 : sc0);
      else wg_g1_n112(acc, a + k * 128, b + k * 128, (h | k) ? 1 : sc0);
    }
    wg_commit();
    if (h == 0) {
      wg_wait<1>();
      if (rel) mbar_arrive(bar + 8 * B_WEMPTY + 8 * (rg.st ? rg.st - 1 : 5));
    }
  }
}
__device__ __forceinline__ void g1_release(uint32_t bar, bool l0, Ring& rg) {
  wg_wait<1>();
  if (l0) mbar_arrive(bar + 8 * B_WEMPTY + 8 * rg.st);
  rg.st += 2;
  if (rg.st == 6) { rg.st = 0; rg.ph ^= 1; }
}

struct G1Tail { RowC rc; uint32_t csa; uint32_t* hp; };

__device__ __forceinline__ void gemm1_phase(const Params& p, uint32_t sb, int layer, int w, int wp, int lane, int ti, int tj,
                                            float (&accA)[64], float (&accB)[64], G1Tail& tl) {
  const uint32_t bar = sb + SM_BAR;
  const bool l0 = lane == 0;
#pragma unroll
  for (int i = 0; i < 64; i++) { accA[i] = 0.f; accB[i] = 0.f; }
  pin_regs(accA); pin_regs(accB);
  const uint32_t dx = desc_lo(sb + SM_X + w * 8192, 1024), dw = desc_lo(sb + SM_WR, 8192);
  Ring rg; rg.st = 0; rg.ph = 0;
#pragma unroll 1
  for (int kb = 0; kb < 4; kb += 2) {
    g1_mma2<0, true>(accA, bar, dx, dw, kb, kb, l0 && kb > 0, rg, layer);
    if (kb == 0) TS(9 + 20 * layer);
    g1_release(bar, l0, rg);
  }
#pragma unroll 1
  for (int kb = 0; kb < 4; kb += 2) {
    g1_mma2<0, false>(accB, bar, dx, dw, kb, kb, l0, rg, layer);
    g1_release(bar, l0, rg);
  }
  TS(18 + 20 * layer);
#pragma unroll 1
  for (int kb = 4; kb < 8; kb += 2) {
    g1_mma2<0, true>(accA, bar, dx, dw, kb, 1, l0, rg, layer);
    g1_release(bar, l0, rg);
  }
  TS(10 + 20 * layer);
  RowC& rc = tl.rc;
  uint32_t* hp = reinterpret_cast<uint32_t*>(p.sc->h) + (ti * 24 + tj) * 4096 + (8 * w + 2 * wp) * 32 + lane;
  const uint32_t csa = sb + SM_CS + 2 * (lane & 3) * 4;
  mbar_wait(bar + 8 * B_STFULL, layer);
  if (layer == 0) mbar_wait(bar + 8 * B_CSFULL, 0);
#pragma unroll
  for (int hh = 0; hh < 2; hh++) {
    const float2 mr = ldsf2(sb + SM_ST + (w * 64 + 16 * wp + (lane >> 2) + 8 * hh) * 8);
    rc.a1[hh] = -1.4426950408889634f * mr.y; rc.b1[hh] = 1.4426950408889634f * mr.y * mr.x;
    rc.r[hh] = mr.y; rc.rm[hh] = -mr.y * mr.x;
  }
  if (w == 1) bar_sync(6, 256);
#define G1_IT(ACC, SRC, NV, KB, SC0, NB, CS, HP, FIRST)                        \
  {                                                                            \
    CsV c, c2;                                                                 \
    g1_ldcs(c, (CS) + (NB) * 32);                                              \
    g1_mma2<NV, false>(ACC, bar, dx, dw, KB, SC0, l0, rg, 0);                  \
    if (FIRST) { pin_regs(SRC); if (w == 0) bar_arrive(6, 256); }              \
    g1_ldcs(c2, (CS) + (NB) * 32 + 64);                                        \
    g1_slice<NB>(SRC, c, rc, HP);                                              \
    g1_slice<NB + 2>(SRC, c2, rc, HP);                                         \
    g1_release(bar, l0, rg);                                                   \
  }
  G1_IT(accB, accA, 0, 4, 1, 0, csa, hp, true)
  G1_IT(accB, accA, 0, 6, 1, 4, csa, hp, false)
  __syncwarp();
  if (l0) mbar_arrive(bar + 8 * (B_PUB + 2 * w));
  TS(11 + 20 * layer);
  if (w == 1) bar_sync(6, 256);
  G1_IT(accA, accB, 1, 0, 0, 0, csa + 256, hp + 8 * 4096, true)
  G1_IT(accA, accB, 1, 2, 1, 4, csa + 256, hp + 8 * 4096, false)
#undef G1_IT
  __syncwarp();
  if (l0) mbar_arrive(bar + 8 * (B_PUB + 2 * w + 1));
#pragma unroll 1
  for (int kb = 4; kb < 8; kb += 2) {
    g1_mma2<1, false>(accA, bar, dx, dw, kb, 1, l0, rg, 0);
    g1_release(bar, l0, rg);
  }
  wg_wait<0>();
  pin_regs(accA);
  if (l0) { mbar_arrive(bar + 8 * B_WEMPTY + 8 * 5); mbar_arrive(bar + 8 * B_G1DONE); }
  TS(12 + 20 * layer);
  tl.csa = csa + 512;
  tl.hp = hp + 16 * 4096;
}

__device__ __forceinline__ void gemm2_phase(const Params& p, uint32_t sb, int layer, int w, int wp, int lane, int tt, int tq, uint32_t rank,
                                            int tj, float (&big)[64], const float (&prv)[64], const G1Tail& tl) {
  const uint32_t bar = sb + SM_BAR;
  const int t = wp * 32 + lane;
  if (w == 0 && t == 0) mbar_expect(bar + 8 * B_RECV, 32768);
  {
    CsV c0, c1, c2;
    g1_ldcs(c0, tl.csa); g1_ldcs(c1, tl.csa + 64); g1_ldcs(c2, tl.csa + 128);
    g1_slice<0>(prv, c0, tl.rc, tl.hp);
    if (tj < 7) { g1_slice<2>(prv, c1, tl.rc, tl.hp); g1_slice<4>(prv, c2, tl.rc, tl.hp); }
    __syncwarp();
    if (lane == 0) mbar_arrive(bar + 8 * (B_PUB + 2 * w));
    TS(13 + 20 * layer);
  }
  uint32_t stage = 0, phase = 0;
#pragma unroll 1
  for (int n = 0; n < 12; n++) {
    mbar_wait_fast(bar + 8 * (B_G2FULL + stage), phase);
    if (n == 0) TS(14 + 20 * layer);
    if (n == 8) TS(19 + 20 * layer);
    const uint32_t sa = sb + g2_stage_off(stage);
    const uint32_t da = desc_lo(sa + w * 8192, 1024), db = desc_lo(sa + 16384, 2048);
    if (n < 8) {
      wg_fence();
#pragma unroll
      for (int k = 0; k < 4; k++) wg_g2_n128(big, da + k * 128, db + k * 256, (n | k) != 0);
      wg_commit();
    } else if (n < 11 || rank == 0) {
      wg_fence();
#pragma unroll
      for (int k = 0; k < 3; k++) wg_g2_n128(big, da + k * 128, db + k * 256, 1);
      wg_commit();
    } else {
      wg_fence();
      wg_g2_n128(big, da, db, 1);
      wg_commit();
    }
    wg_wait<1>();
    if (lane == 0) {
      if (n > 0 && n <= 6) mbar_arrive(bar + 8 * (B_G2EMPTY + n - 1));
      if (n == 7) mbar_arrive_remote(peer_addr(bar + 8 * B_PEERRDY, rank ^ 1));
    }
    if (++stage == 6) { stage = 0; phase ^= 1; }
  }
  wg_wait<0>();
  pin_regs(big);
  TS(15 + 20 * layer);
  float acc[32];
  {
    const uint32_t off = SM_XB + w * 16384 + t * 16, soff = SM_XS2 + w * 16384;
#pragma unroll
    for (int i = 0; i < 8; i++) {
      const int o = 4 * i;
      sts128(sb + soff + t * 16 + i * 2048,
             rank ? make_uint4(__float_as_uint(big[o]), __float_as_uint(big[o + 1]), __float_as_uint(big[o + 2]), __float_as_uint(big[o + 3]))
                  : make_uint4(__float_as_uint(big[32 + o]), __float_as_uint(big[33 + o]), __float_as_uint(big[34 + o]), __float_as_uint(big[35 + o])));
    }
    fence_async_smem();
    bar_sync(1 + w, 128);
    if (wp == 0 && elect_one()) {
      mbar_wait(bar + 8 * B_PEERRDY, layer);
      asm volatile("cp.async.bulk.shared::cluster.shared::cta.mbarrier::complete_tx::bytes [%0], [%1], 16384, [%2];"
                   ::"r"(peer_addr(sb + SM_XB + w * 16384, rank ^ 1)), "r"(sb + soff), "r"(peer_addr(bar + 8 * B_RECV, rank ^ 1)) : "memory");
    }
    if (layer) TS(57);
    mbar_wait(bar + 8 * B_RECV, layer);
    if (layer) TS(58);
#pragma unroll
    for (int i = 0; i < 8; i++) {
      const uint4 v = lds128(sb + off + i * 2048);
      acc[4 * i] = __uint_as_float(v.x) + (rank ? big[32 + 4 * i] : big[4 * i]);
      acc[4 * i + 1] = __uint_as_float(v.y) + (rank ? big[32 + 4 * i + 1] : big[4 * i + 1]);
      acc[4 * i + 2] = __uint_as_float(v.z) + (rank ? big[32 + 4 * i + 2] : big[4 * i + 2]);
      acc[4 * i + 3] = __uint_as_float(v.w) + (rank ? big[32 + 4 * i + 3] : big[4 * i + 3]);
    }
  }
  mbar_wait(bar + 8 * B_RESFULL, layer);
  const int g = lane >> 2, c = lane & 3;
  const int mat = lane >> 3;
  const int rrow = 64 * w + 16 * wp + (lane & 7) + 8 * (mat & 1);
  const uint32_t ra = sb + SM_RES + rrow * 128;
  uint32_t o[16];
#pragma unroll
  for (int nb = 0; nb < 8; nb += 2) {
    uint32_t r0, r1, r2, r3;
    ldsm4(ra + (((nb + (mat >> 1)) ^ (rrow & 7)) << 4), r0, r1, r2, r3);
    const uint32_t rr[4] = {r0, r1, r2, r3};
#pragma unroll
    for (int k = 0; k < 4; k++) {
      const int a = 4 * (nb + (k >> 1)) + 2 * (k & 1);
      o[2 * nb + k] = bf2_add(rr[k], pack_bf(acc[a], acc[a + 1]));
    }
  }
  if (layer == 0) {
#pragma unroll
    for (int nb = 0; nb < 8; nb += 2)
      stsm4(ra + (((nb + (mat >> 1)) ^ (rrow & 7)) << 4), o[2 * nb], o[2 * nb + 1], o[2 * nb + 2], o[2 * nb + 3]);
    __syncwarp();
#pragma unroll
    for (int i = 0; i < 4; i++) {
      const int idx = lane + 32 * i, row = 64 * w + 16 * wp + (idx >> 3), ch = idx & 7;
      const uint4 v = lds128(sb + SM_RES + row * 128 + ((ch ^ (row & 7)) << 4));
      *reinterpret_cast<uint4*>(p.sc->xT[1] + (128 * tq + row) * SEQ + 64 * tt + 8 * ch) = v;
    }
    float v[32];
#pragma unroll
    for (int nb = 0; nb < 8; nb++) {
      const uint32_t a = o[2 * (nb & ~1) + 2 * (nb & 1)], b = o[2 * (nb & ~1) + 2 * (nb & 1) + 1];
      const float a0 = bf_lo(a), a1 = bf_hi(a), b0 = bf_lo(b), b1 = bf_hi(b);
      v[4 * nb] = a0 + b0; v[4 * nb + 1] = a1 + b1;
      v[4 * nb + 2] = fmaf(a0, a0, b0 * b0); v[4 * nb + 3] = fmaf(a1, a1, b1 * b1);
    }
    const bool s4 = lane & 16, s3 = lane & 8, s2 = lane & 4;
#pragma unroll
    for (int i = 0; i < 16; i++) {
      const float snd = s4 ? v[i] : v[16 + i], kp = s4 ? v[16 + i] : v[i];
      v[i] = kp + __shfl_xor_sync(0xffffffffu, snd, 16);
    }
#pragma unroll
    for (int i = 0; i < 8; i++) {
      const float snd = s3 ? v[i] : v[8 + i], kp = s3 ? v[8 + i] : v[i];
      v[i] = kp + __shfl_xor_sync(0xffffffffu, snd, 8);
    }
#pragma unroll
    for (int i = 0; i < 4; i++) {
      const float snd = s2 ? v[i] : v[4 + i], kp = s2 ? v[4 + i] : v[i];
      v[i] = kp + __shfl_xor_sync(0xffffffffu, snd, 4);
    }
    {
      const int nbf = (s4 ? 4 : 0) + (s3 ? 2 : 0) + (s2 ? 1 : 0), col = 8 * nbf + 2 * c;
      const uint32_t scr = sb + SM_G2S + (w * 4 + wp) * 512 + col * 8;
      stsf2(scr, v[0], v[2]);
      stsf2(scr + 8, v[1], v[3]);
    }
    bar_sync(4, 256);
    if (w == 0) {
      float s = 0.f;
#pragma unroll
      for (int k = 0; k < 8; k++) s += ldsf(sb + SM_G2S + k * 512 + t * 4);
      atomicAdd(reinterpret_cast<float*>(p.sc->stat3) + 128 * tt + t, s);
    }
    __syncwarp();
    if (lane == 0) mbar_arrive(bar + 8 * (B_PUB + 2 * w + 1));
    fence_async_smem();
    __syncwarp();
    if (lane == 0) mbar_arrive(bar + 8 * B_G2DONE);
  } else {
    const uint32_t oa = sb + SM_G2S + w * 8192;
#pragma unroll
    for (int nb = 0; nb < 8; nb += 2) {
      const int l = 8 * (nb + (mat >> 1)) + (lane & 7), chunk = 2 * wp + (mat & 1);
      stsm4t(oa + l * 128 + ((chunk ^ (l & 7)) << 4), o[2 * nb], o[2 * nb + 1], o[2 * nb + 2], o[2 * nb + 3]);
    }
    bar_sync(1 + w, 128);
#pragma unroll
    for (int i = 0; i < 4; i++) {
      const int idx = t + 128 * i, l = idx >> 3, ch = idx & 7;
      const uint4 v = lds128(oa + l * 128 + ((ch ^ (l & 7)) << 4));
      *reinterpret_cast<uint4*>(p.out + (64 * tt + l) * DM + 128 * tq + 64 * w + 8 * ch) = v;
    }
  }
  TS(16 + 20 * layer);
  (void)g;
}

__global__ void __launch_bounds__(NTHR, 1)
fused_s4d_glu_kernel(const __grid_constant__ CUtensorMap tmG, const __grid_constant__ CUtensorMap tmU, const __grid_constant__ CUtensorMap tmWd,
                     const __grid_constant__ CUtensorMap tmX1, const __grid_constant__ CUtensorMap tmX3,
                     const __grid_constant__ CUtensorMap tmR1, const __grid_constant__ CUtensorMap tmR3,
                     const __grid_constant__ CUtensorMap tmX0, const __grid_constant__ CUtensorMap tmCG,
                     const __grid_constant__ CUtensorMap tmCU, const Params p) {
  extern __shared__ __align__(1024) unsigned char smem[];
  const uint32_t sb = smem_u32(smem);
  const uint32_t bar = sb + SM_BAR;
  const int tid = threadIdx.x, lane = tid & 31;
  const int warp = __shfl_sync(0xffffffffu, tid >> 5, 0);
  const int cta = blockIdx.x;
  const uint32_t rank = cta & 1;
  int ti, tj, ti2, tq, tt;
  auto get_role = [&]() {
    mbar_wait(bar + 8 * B_ROLE, 0);
    const int rho = (int)lds32(sb + SM_ROLE), c2 = 2 * rho + (int)rank;
    const int grp = c2 >> 4, r16 = c2 & 15;
    ti = 4 * (grp & 3) + (r16 & 3); tj = 4 * (grp >> 2) + (r16 >> 2);
    ti2 = rho >> 2; tq = rho & 3; tt = 2 * ti2 + (int)rank;
  };
  TS(2);
  uint32_t kraw[10];
  if (warp < 8) {
#pragma unroll
    for (int v = 0; v < 2; v++) {
      const int ch = 4 * cta + 2 * v + (warp >> 2), idx = ch * NMODE + (tid & 127);
      asm volatile("ld.global.nc.u16 %0, [%1];" : "=r"(kraw[5 * v]) : "l"(p.logA + idx));
      asm volatile("ld.global.nc.u16 %0, [%1];" : "=r"(kraw[5 * v + 1]) : "l"(p.Aim + idx));
      asm volatile("ld.global.nc.u16 %0, [%1];" : "=r"(kraw[5 * v + 2]) : "l"(p.Cre + idx));
      asm volatile("ld.global.nc.u16 %0, [%1];" : "=r"(kraw[5 * v + 3]) : "l"(p.Cim + idx));
      asm volatile("ld.global.nc.u16 %0, [%1];" : "=r"(kraw[5 * v + 4]) : "l"(p.logdt + ch));
    }
  }
  uint4 xrow[8];
  if (warp >= 8) {
#pragma unroll
    for (int r = 0; r < 4; r++) {
      const bf16* src = p.x0 + (16 * cta + 4 * (warp - 8) + r) * DM + lane * 8;
      xrow[2 * r] = ldg128_nc(src); xrow[2 * r + 1] = ldg128_nc(src + 256);
    }
  }
  if (warp >= 8 && lane == 0) {
    if (sb & 1023) __trap();
    const uint32_t codes = warp == 8 ? (uint32_t)LO_CODES : (warp == 9 ? (uint32_t)(LO_CODES >> 32) : (warp == 10 ? (uint32_t)HI_CODES : (uint32_t)(HI_CODES >> 32)));
    const uint32_t b0 = bar + (warp - 8) * 128;
#pragma unroll
    for (int i = 0; i < 16; i++) mbar_init(b0 + 8 * i, 1u << ((codes >> (2 * i)) & 3));
    asm volatile("fence.mbarrier_init.release.cluster;" ::: "memory");
  }
  asm volatile("barrier.cluster.arrive.relaxed.aligned;\nbarrier.cluster.wait.aligned;" ::: "memory");

  if (warp < 8) {
    asm volatile("setmaxnreg.inc.sync.aligned.u32 224;");
    TS(0);
    const int w = warp >> 2, wp = warp & 3;
    const int t = wp * 32 + lane;
    KParam kp[2];
#pragma unroll
    for (int v = 0; v < 2; v++) {
      uint32_t f[5];
#pragma unroll
      for (int k = 0; k < 5; k++) asm volatile("shl.b32 %0, %1, 16;" : "=r"(f[k]) : "r"(kraw[5 * v + k]));
      kp[v].logA = __uint_as_float(f[0]); kp[v].aim = __uint_as_float(f[1]); kp[v].cre = __uint_as_float(f[2]);
      kp[v].cim = __uint_as_float(f[3]); kp[v].logdt = __uint_as_float(f[4]);
    }
    float kinv[2];
    kgen(sb, w, wp, lane, kp, kinv);
    strip_transpose(sb, warp, lane, cta);
    TS(1);
#pragma unroll 1
    for (int layer = 0; layer < 2; layer++) {
      conv_phase(p, sb, layer, w, wp, lane, cta, kinv[0], kinv[1]);
      get_role();
      float accA[64], accB[64];
      G1Tail tl;
      gemm1_phase(p, sb, layer, w, wp, lane, ti, tj, accA, accB, tl);
      gemm2_phase(p, sb, layer, w, wp, lane, tt, tq, rank, tj, accB, accA, tl);
    }
    __syncwarp();
    if (lane == 0) mbar_arrive(bar + 8 * B_KDONE);
  } else {
    asm volatile("setmaxnreg.dec.sync.aligned.u32 56;");
    const int wv = warp - 8;
    unsigned ep1;
    asm volatile("ld.relaxed.gpu.global.u32 %0, [%1];" : "=r"(ep1) : "l"(&p.sc->epoch) : "memory");
    ep1 += 1;
    {
      uint4 (&v)[8] = xrow;
      if (wv == 0 && elect_one()) {
        const uint32_t fb = bar + 8 * B_STRIP;
        mbar_expect(fb, 32768);
#pragma unroll 1
        for (int k = 0; k < 4; k++) tma_2d_mc(sb + SM_STRIP + (4 * rank + k) * 4096, &tmX0, 8 * (cta >> 1), 256 * (4 * rank + k), fb);
      }
      __syncwarp();
      if (lane < 9) {
        float2* z = (lane == 0 ? p.sc->stat3 : p.sc->stat2[(lane - 1) >> 2][(lane - 1) & 3]) + 16 * cta + 4 * wv;
        *reinterpret_cast<uint4*>(z) = make_uint4(0, 0, 0, 0);
        *reinterpret_cast<uint4*>(z + 2) = make_uint4(0, 0, 0, 0);
      }
      float a[8];
#pragma unroll
      for (int r = 0; r < 4; r++) {
        const uint32_t xx[8] = {v[2 * r].x, v[2 * r].y, v[2 * r].z, v[2 * r].w, v[2 * r + 1].x, v[2 * r + 1].y, v[2 * r + 1].z, v[2 * r + 1].w};
        float s0 = 0.f, s1 = 0.f, q0 = 0.f, q1 = 0.f;
#pragma unroll
        for (int k = 0; k < 8; k++) { const float lo = bf_lo(xx[k]), hi = bf_hi(xx[k]); s0 += lo; s1 += hi; q0 = fmaf(lo, lo, q0); q1 = fmaf(hi, hi, q1); }
        a[2 * r] = s0 + s1; a[2 * r + 1] = q0 + q1;
      }
      const bool s4 = lane & 16, s3 = lane & 8, s2 = lane & 4;
#pragma unroll
      for (int i = 0; i < 4; i++) { const float snd = s4 ? a[i] : a[4 + i], kp2 = s4 ? a[4 + i] : a[i]; a[i] = kp2 + __shfl_xor_sync(0xffffffffu, snd, 16); }
#pragma unroll
      for (int i = 0; i < 2; i++) { const float snd = s3 ? a[i] : a[2 + i], kp2 = s3 ? a[2 + i] : a[i]; a[i] = kp2 + __shfl_xor_sync(0xffffffffu, snd, 8); }
      { const float snd = s2 ? a[0] : a[1], kp2 = s2 ? a[1] : a[0]; a[0] = kp2 + __shfl_xor_sync(0xffffffffu, snd, 4); }
      a[0] += __shfl_xor_sync(0xffffffffu, a[0], 2);
      a[0] += __shfl_xor_sync(0xffffffffu, a[0], 1);
      if ((lane & 3) == 0) reinterpret_cast<float*>(p.sc->stat1)[2 * (16 * cta + 4 * wv) + (lane >> 2)] = a[0];
      if (wv == 0 && lane == 0 && rank == 0) {
        unsigned smid;
        asm volatile("mov.u32 %0, %%smid;" : "=r"(smid));
        const unsigned k = smid >> 1;
        const unsigned gpc = k < 32 ? (k & 7) : (k < 60 ? 1 + (k - 32) % 7 : (k < 62 ? k - 54 : k - 61));
        p.sc->tpc[cta >> 1] = gpc * 256 + k;
      }
      bar_sync(3, 128);
      if (wv == 0 && lane == 0) TSA(21);
    }
    if (wv == 3) {
      {
        mbar_wait(bar + 8 * B_F0OK, 0);
        unsigned k0, k1, me;
        asm volatile("ld.global.cg.u32 %0, [%1];" : "=r"(k0) : "l"(&p.sc->tpc[lane]) : "memory");
        asm volatile("ld.global.cg.u32 %0, [%1];" : "=r"(k1) : "l"(&p.sc->tpc[32 + lane]) : "memory");
        asm volatile("ld.global.cg.u32 %0, [%1];" : "=r"(me) : "l"(&p.sc->tpc[cta >> 1]) : "memory");
        const int pc = cta >> 1;
        const bool b0 = k0 < me || (k0 == me && lane < pc), b1 = k1 < me || (k1 == me && 32 + lane < pc);
        const int rho = __popc(__ballot_sync(0xffffffffu, b0)) + __popc(__ballot_sync(0xffffffffu, b1));
        if (lane == 0) { sts32(sb + SM_ROLE, (uint32_t)rho); mbar_arrive(bar + 8 * B_ROLE); }
        __syncwarp();
        get_role();
      }
      if (elect_one()) {
        mbar_wait(bar + 8 * B_PTDONE, 0);
        asm volatile("cp.async.bulk.global.shared::cta.bulk_group [%0], [%1], %2;" ::"l"(p.sc->ptab + 4 * cta * PTW), "r"(sb + SM_PT), "n"(4 * PTW * 4) : "memory");
        asm volatile("cp.async.bulk.commit_group;" ::: "memory");
        asm volatile("cp.async.bulk.wait_group 0;" ::: "memory");
        fence_async_all();
        mbar_arrive(bar + 8 * B_PTSAVED);
      }
      __syncwarp();
      if (elect_one()) {
        mbar_wait(bar + 8 * B_CSDONE, 0);
        flag_wait(&p.sc->flag[F_CS * 8], ep1 * 172);
        fence_async_all();
        const uint32_t fb = bar + 8 * B_CSFULL;
        mbar_expect(fb, 1408);
        bulk_g2s(sb + SM_CS, p.sc->cs + 176 * tj, 704, fb);
        bulk_g2s(sb + SM_CS + 704, p.sc->cs + CSP + 176 * tj, 704, fb);
      }
      __syncwarp();
#pragma unroll 1
      for (int layer = 0; layer < 2; layer++) {
        if (elect_one()) {
          mbar_wait(bar + 8 * B_STAGED, layer);
          asm volatile("cp.reduce.async.bulk.global.shared::cta.bulk_group.add.f32 [%0], [%1], 16384;" ::"l"(p.sc->stat2[layer][cta & 3]), "r"(sb + SM_MISC) : "memory");
          asm volatile("cp.async.bulk.commit_group;" ::: "memory");
          asm volatile("cp.async.bulk.wait_group.read 0;" ::: "memory");
          mbar_arrive(bar + 8 * B_TAILDONE);
          asm volatile("cp.async.bulk.wait_group 0;" ::: "memory");
          fence_async_all();
          flag_publish(&p.sc->flag[(F_S + layer) * 8]);
          flag_wait(&p.sc->flag[(F_S + layer) * 8], ep1 * 128);
        }
        __syncwarp();
#pragma unroll 1
        for (int k0 = 0; k0 < 4; k0 += 2) {
          float2 v[8];
#pragma unroll
          for (int k = 0; k < 2; k++) {
            const int l = 128 * ti + 32 * (k0 + k) + lane, tq16 = l >> 4;
            const float* src = reinterpret_cast<const float*>(p.sc->stat2[layer]) + tq16 * 32 + ((((l & 15) >> 1) ^ (tq16 & 7)) << 2) + (l & 1) * 2;
#pragma unroll
            for (int r = 0; r < 4; r++) asm volatile("ld.global.cg.v2.f32 {%0, %1}, [%2];" : "=f"(v[4 * k + r].x), "=f"(v[4 * k + r].y) : "l"(src + r * 2 * SEQ) : "memory");
          }
#pragma unroll
          for (int k = 0; k < 2; k++) {
            const float2 mr = ln_finalize((v[4 * k].x + v[4 * k + 1].x) + (v[4 * k + 2].x + v[4 * k + 3].x), (v[4 * k].y + v[4 * k + 1].y) + (v[4 * k + 2].y + v[4 * k + 3].y));
            stsf2(sb + SM_ST + (32 * (k0 + k) + lane) * 8, mr.x, mr.y);
          }
        }
        __syncwarp();
        if (lane == 0) mbar_arrive(bar + 8 * B_STFULL);
      }
      if (lane == 0) mbar_wait_checked(bar + 8 * B_KDONE, 0);
    } else if (wv == 1 || wv == 2) {
      const int unit = cta + 128 * (wv - 1);
      if (unit < 172) {
        const int mat = unit / 86, col0 = (unit - mat * 86) * 16;
        const uint32_t buf = sb + SM_X + (wv - 1) * 16384, lb = bar + 8 * (B_CSL + wv - 1);
        if (elect_one()) {
          mbar_wait(bar + 8 * B_KGDONE, 0);
          mbar_expect(lb, 16384);
          tma_2d(buf, mat ? &tmCU : &tmCG, col0, 0, lb);
          tma_2d(buf + 8192, mat ? &tmCU : &tmCG, col0, 256, lb);
        }
        __syncwarp();
        mbar_wait(lb, 0);
        float a[8];
#pragma unroll
        for (int k = 0; k < 8; k++) a[k] = 0.f;
#pragma unroll 4
        for (int i = 0; i < 32; i++) {
          const uint4 v = lds128(buf + i * 512 + lane * 16);
          a[0] += bf_lo(v.x); a[1] += bf_hi(v.x); a[2] += bf_lo(v.y); a[3] += bf_hi(v.y);
          a[4] += bf_lo(v.z); a[5] += bf_hi(v.z); a[6] += bf_lo(v.w); a[7] += bf_hi(v.w);
        }
#pragma unroll
        for (int k = 0; k < 8; k++)
#pragma unroll
          for (int o = 2; o < 32; o <<= 1) a[k] += __shfl_xor_sync(0xffffffffu, a[k], o);
        if (lane < 2) {
          float4* dst = reinterpret_cast<float4*>(p.sc->cs + mat * CSP + col0 + lane * 8);
          dst[0] = make_float4(a[0], a[1], a[2], a[3]);
          dst[1] = make_float4(a[4], a[5], a[6], a[7]);
        }
        __syncwarp();
        if (elect_one()) { flag_publish(&p.sc->flag[F_CS * 8]); if (wv == 1) TSA(41); }
        __syncwarp();
      }
      if (lane == 0) mbar_arrive(bar + 8 * B_CSDONE);
      __syncwarp();
      if (elect_one()) {
        get_role();
        const int w = wv - 1;
#pragma unroll 1
        for (int layer = 0; layer < 2; layer++) {
#pragma unroll 1
          for (int e = 0; e < (layer == 0 ? 6 : 5); e++) {
            mbar_wait(bar + 8 * (B_PUB + 2 * w + (e & 1)), (3 * layer + (e >> 1)) & 1);
            const int f = e < 2 ? F_1 + layer * 2 + e : (e < 5 ? F_2 + layer * 48 + ti * 3 + (e - 2) : F_3);
            if (layer == 1 && e == 4 && w == 0) TSA(56);
            flag_publish(&p.sc->flag[f * 8]);
            if (layer == 1 && e == 4 && w == 0) TSA(49);
            if (e == 4) mbar_arrive(bar + 8 * B_PUBDONE);
            if (e == 5) mbar_arrive(bar + 8 * B_PUB3);
          }
        }
      }
    } else if (elect_one()) {
      flag_publish(&p.sc->flag[F_0 * 8]);
      TSA(22);
      tmap_prefetch(&tmG); tmap_prefetch(&tmU); tmap_prefetch(&tmX1); tmap_prefetch(&tmWd);
      tmap_prefetch(&tmR1); tmap_prefetch(&tmX3); tmap_prefetch(&tmR3);
      l2_prefetch(reinterpret_cast<const char*>(p.wd) + cta * 11008, 11008);
      uint32_t wst = 0, wph = 1;
      auto issue_w = [&](int n) {
        TRA(n * 4);
        mbar_wait(bar + 8 * (B_WEMPTY + wst), wph);
        const uint32_t fb = bar + 8 * (B_WFULL + wst), dst = sb + SM_WR + wst * 16384;
        const int pp = n < 16 ? (n >> 2) & 1 : 2, kb = n < 16 ? (n & 3) + ((n >> 1) & 4) : n - 16;
        const int f0 = 176 * tj + 64 * pp;
        mbar_expect(fb, 16384);
        tma_4d(dst, &tmG, f0, 0, kb >> 2, 32 * (kb & 3), fb);
        tma_4d(dst + 8192, &tmU, f0, 0, kb >> 2, 32 * (kb & 3), fb);
        if (++wst == 6) { wst = 0; wph ^= 1; }
      };
#pragma unroll 1
      for (int layer = 0; layer < 2; layer++) {
        const CUtensorMap* tmX = layer ? &tmX3 : &tmX1;
        {
          flag_wait(&p.sc->flag[(layer ? F_3 : F_0) * 8], ep1 * (layer ? 256 : 128));
          TSA(layer ? 48 : 40);
          if (layer == 0) mbar_arrive(bar + 8 * B_F0OK);
          fence_async_all();
          const uint32_t fb = bar + 8 * B_XSFULL;
          if (layer == 0) {
            if (cta == 0) asm volatile("st.relaxed.gpu.global.u32 [%0], %1;" ::"l"(&p.sc->epoch), "r"(ep1) : "memory");
            mbar_wait(bar + 8 * B_KGDONE, 0);
            mbar_expect(fb, 16384);
          } else {
            mbar_expect(fb, 32768);
            bulk_g2s(sb + CV_XS, p.sc->xT[1] + 4 * cta * SEQ, 16384, fb);
          }
          bulk_g2s(sb + CV_B97, layer ? p.sc->stat3 : p.sc->stat1, 16384, fb);
          if (layer == 0) {
            get_role();
            issue_w(0);
            mbar_wait(bar + 8 * B_STRIPDONE, 0);
          } else {
            mbar_wait(fb, 1);
            const uint32_t pb = bar + 8 * B_PTFULL;
            mbar_expect(pb, 4 * PTW * 4);
            bulk_g2s(sb + SM_PT, p.sc->ptab + 4 * cta * PTW, 4 * PTW * 4, pb);
            issue_w(0);
          }
          issue_w(1);
          issue_w(2);
        }
        if (layer == 0) mbar_wait(bar + 8 * B_CSDONE, 0);
#pragma unroll 1
        for (int b = 0; b < 2; b++) {
          if (b == 1) {
            TSA(42 + 8 * layer);
            mbar_wait(bar + 8 * B_CONVDONE, layer);
            if (layer == 0) mbar_wait(bar + 8 * B_PTSAVED, 0);
            issue_w(3);
            issue_w(4);
            mbar_wait(bar + 8 * B_TAILDONE, layer);
            issue_w(5);
            issue_w(6);
            issue_w(7);
          }
          flag_wait(&p.sc->flag[(F_1 + layer * 2 + b) * 8], ep1 * 256);
          if (layer == 1 && b == 1) TSA(59);
          fence_async_all();
#pragma unroll 1
          for (int k = 0; k < 4; k++) {
            const uint32_t fb = bar + 8 * (B_XFULL + 4 * b + k);
            mbar_expect(fb, 16384);
            tma_5d(sb + SM_X + (4 * b + k) * 16384, tmX, 0, 0, b, 32 * k, 2 * ti, fb);
          }
        }
        TSA(43 + 8 * layer);
#pragma unroll 1
        for (int n = 8; n < 24; n++) issue_w(n);
        uint32_t st2 = 0;
        const bf16* hsrc = p.sc->h + (ti2 * 24 + 4 * rank) * 8192;
        const unsigned* f2 = &p.sc->flag[(F_2 + layer * 48 + ti2 * 3) * 8];
        flag_wait(f2, ep1 * 16);
        TSA(45 + 8 * layer);
        fence_async_all();
#pragma unroll 1
        for (int n = 0; n < 12; n++) {
          const int pp = n >> 2, j = 4 * rank + (n & 3);
          const uint32_t fb = bar + 8 * (B_G2FULL + st2), dst = sb + g2_stage_off(st2);
          const uint32_t hbytes = pp < 2 ? 16384 : (j < 7 ? 12288 : 4096);
          if ((n & 3) == 0 && pp > 0) { flag_wait(f2 + pp * 8, ep1 * 16); fence_async_all(); TSA(45 + pp + 8 * layer); }
          if (n < 3) {
            mbar_wait(bar + 8 * (B_WEMPTY + 2 * n), 1);
            mbar_wait(bar + 8 * (B_WEMPTY + 2 * n + 1), 1);
          } else if (n == 3) {
            mbar_wait(bar + 8 * B_G1DONE, layer);
            TSA(44 + 8 * layer);
          } else if (n == 5) {
            mbar_wait(bar + 8 * B_PUBDONE, layer);
          } else if (n >= 6) {
            mbar_wait(bar + 8 * (B_G2EMPTY + st2), layer);
          }
          mbar_expect(fb, 16384 + hbytes);
          tma_3d(dst, &tmWd, 0, 176 * j + 64 * pp, 2 * tq, fb);
          bulk_g2s(dst + 16384, hsrc + (pp * 8 + (n & 3)) * 8192, hbytes, fb);
          if (n == 5) {
            const uint32_t rb = bar + 8 * B_RESFULL;
            mbar_expect(rb, 16384);
            tma_2d(sb + SM_RES, layer ? &tmR3 : &tmR1, 64 * tt, 128 * tq, rb);
          }
          if (++st2 == 6) st2 = 0;
        }
        if (layer == 0) { mbar_wait(bar + 8 * B_G2DONE, 0); mbar_wait(bar + 8 * B_PUB3, 0); }
      }
    }
  }
}

typedef CUresult (*EncodeFn)(CUtensorMap*, CUtensorMapDataType, cuuint32_t, void*, const cuuint64_t*, const cuuint64_t*, const cuuint32_t*,
                             const cuuint32_t*, CUtensorMapInterleave, CUtensorMapSwizzle, CUtensorMapL2promotion, CUtensorMapFloatOOBfill);

void make_map(EncodeFn fn, CUtensorMap* m, const void* base, int rank, const cuuint64_t* dims, const cuuint64_t* strides, const cuuint32_t* box) {
  cuuint32_t es[5] = {1, 1, 1, 1, 1};
  fn(m, CU_TENSOR_MAP_DATA_TYPE_BFLOAT16, rank, const_cast<void*>(base), dims, strides, box, es, CU_TENSOR_MAP_INTERLEAVE_NONE,
     CU_TENSOR_MAP_SWIZZLE_128B, CU_TENSOR_MAP_L2_PROMOTION_L2_128B, CU_TENSOR_MAP_FLOAT_OOB_FILL_NONE);
}

}

extern "C" void kernel_launch(void* const* d_in, const int* in_sizes, int n_in, void* d_out, int out_size) {
  (void)in_sizes; (void)n_in; (void)out_size;
  static EncodeFn enc = nullptr;
  static Scratch* sc = nullptr;
  if (!enc) {
    void* fn = nullptr;
    cudaDriverEntryPointQueryResult qr;
    cudaGetDriverEntryPoint("cuTensorMapEncodeTiled", &fn, cudaEnableDefault, &qr);
    enc = (EncodeFn)fn;
    void* a = nullptr;
    cudaGetSymbolAddress(&a, g_scratch);
    sc = (Scratch*)a;
    cudaFuncSetAttribute(fused_s4d_glu_kernel, cudaFuncAttributeMaxDynamicSharedMemorySize, SM_TOTAL);
  }
  Params p;
  p.x0 = (const bf16*)d_in[0]; p.logA = (const bf16*)d_in[1]; p.Aim = (const bf16*)d_in[2]; p.Cre = (const bf16*)d_in[3];
  p.Cim = (const bf16*)d_in[4]; p.logdt = (const bf16*)d_in[5]; p.Dsk = (const bf16*)d_in[6];
  p.wg = (const bf16*)d_in[8]; p.wu = (const bf16*)d_in[9]; p.wd = (const bf16*)d_in[10];
  p.out = (bf16*)d_out;
  p.sc = sc;
  bf16* xT = &sc->xT[0][0];

  CUtensorMap tmG, tmU, tmWd, tmX1, tmX3, tmR1, tmR3, tmX0, tmCG, tmCU;
  {
    const cuuint64_t dims[4] = {FF, 2, 2, 128}, str[3] = {FF * 2, FF * 4, FF * 8};
    const cuuint32_t box[4] = {64, 2, 1, 32};
    make_map(enc, &tmG, p.wg, 4, dims, str, box);
    make_map(enc, &tmU, p.wu, 4, dims, str, box);
  }
  {
    const cuuint64_t dims[3] = {64, FF, 8}, str[2] = {DM * 2, 128};
    const cuuint32_t box[3] = {64, 64, 2};
    make_map(enc, &tmWd, p.wd, 3, dims, str, box);
  }
  {
    const cuuint64_t dims[5] = {64, 2, 2, 128, 32}, str[4] = {SEQ * 2, SEQ * 4, SEQ * 8, 128};
    const cuuint32_t box[5] = {64, 2, 1, 32, 2};
    make_map(enc, &tmX1, xT, 5, dims, str, box);
    make_map(enc, &tmX3, xT + 2 * DM * SEQ, 5, dims, str, box);
  }
  {
    const cuuint64_t dims[2] = {SEQ, DM}, str[1] = {SEQ * 2};
    const cuuint32_t box[2] = {64, 128};
    make_map(enc, &tmR1, xT, 2, dims, str, box);
    make_map(enc, &tmR3, xT + 2 * DM * SEQ, 2, dims, str, box);
  }
  {
    const cuuint64_t dims[2] = {DM, SEQ}, str[1] = {DM * 2};
    const cuuint32_t box[2] = {8, 256}, es[2] = {1, 1};
    enc(&tmX0, CU_TENSOR_MAP_DATA_TYPE_BFLOAT16, 2, const_cast<bf16*>(p.x0), dims, str, box, es, CU_TENSOR_MAP_INTERLEAVE_NONE,
        CU_TENSOR_MAP_SWIZZLE_NONE, CU_TENSOR_MAP_L2_PROMOTION_L2_128B, CU_TENSOR_MAP_FLOAT_OOB_FILL_NONE);
  }
  {
    const cuuint64_t dims[2] = {FF, DM}, str[1] = {FF * 2};
    const cuuint32_t box[2] = {16, 256}, es[2] = {1, 1};
    enc(&tmCG, CU_TENSOR_MAP_DATA_TYPE_BFLOAT16, 2, const_cast<bf16*>(p.wg), dims, str, box, es, CU_TENSOR_MAP_INTERLEAVE_NONE,
        CU_TENSOR_MAP_SWIZZLE_NONE, CU_TENSOR_MAP_L2_PROMOTION_L2_128B, CU_TENSOR_MAP_FLOAT_OOB_FILL_NONE);
    enc(&tmCU, CU_TENSOR_MAP_DATA_TYPE_BFLOAT16, 2, const_cast<bf16*>(p.wu), dims, str, box, es, CU_TENSOR_MAP_INTERLEAVE_NONE,
        CU_TENSOR_MAP_SWIZZLE_NONE, CU_TENSOR_MAP_L2_PROMOTION_L2_128B, CU_TENSOR_MAP_FLOAT_OOB_FILL_NONE);
  }
  cudaLaunchConfig_t cfg = {};
  cfg.gridDim = dim3(NCTA); cfg.blockDim = dim3(NTHR); cfg.dynamicSmemBytes = SM_TOTAL; cfg.stream = cudaStreamPerThread;
  cudaLaunchAttribute at[1];
  at[0].id = cudaLaunchAttributeClusterDimension;
  at[0].val.clusterDim.x = 2; at[0].val.clusterDim.y = 1; at[0].val.clusterDim.z = 1;
  cfg.attrs = at; cfg.numAttrs = 1;
  cudaLaunchKernelEx(&cfg, fused_s4d_glu_kernel, tmG, tmU, tmWd, tmX1, tmX3, tmR1, tmR3, tmX0, tmCG, tmCU, p);
}
```

```cpp
#include <cuda_runtime.h>
#include <cuda_bf16.h>
#include <cuda_fp16.h>
#include <cuda.h>
#include <stdint.h>

namespace {

typedef __nv_bfloat16 bf16;

constexpr int SEQ = 2048;
constexpr int DM = 512;
constexpr int NMODE = 128;
constexpr int FF = 1376;
constexpr int NCTA = 128;
constexpr int NTHR = 384;
constexpr int CSP = 1408;
constexpr int PAW = 1152;
constexpr int PTW = 1408;
constexpr int SPIN_LIMIT = 1 << 20;

constexpr uint32_t SM_X = 0;
constexpr uint32_t SM_WR = 131072;
constexpr uint32_t SM_MISC = 212992;
constexpr uint32_t SM_SMALL = 229376;
constexpr uint32_t SM_TOTAL = 232448;
constexpr uint32_t SM_CONV = 65536;
constexpr uint32_t CV_U = SM_CONV;
constexpr uint32_t CV_B97 = SM_CONV + 20480;
constexpr uint32_t CV_E0 = SM_CONV + 36864;
constexpr uint32_t CV_XS = SM_CONV + 49152;
constexpr uint32_t CV_E1 = SM_MISC;
constexpr uint32_t KG_A = 0;
constexpr uint32_t KG_B = 12288;
constexpr uint32_t SM_STRIP = SM_WR + 16384;
constexpr uint32_t SM_PT = SM_WR + 3 * 16384;
constexpr uint32_t SM_STAT = SM_MISC;
constexpr uint32_t SM_RES = 98304;
constexpr uint32_t SM_G2S = 114688;
constexpr uint32_t G2_STAGE = 49152;
constexpr uint32_t SM_BAR = SM_SMALL;
constexpr uint32_t SM_CS = SM_SMALL + 512;
constexpr uint32_t SM_ST = SM_SMALL + 1920;
constexpr uint32_t SM_ROLE = SM_SMALL + 2944;

enum {
  B_WFULL = 0, B_WEMPTY = 6, B_XFULL = 12, B_CSFULL = 20, B_G2FULL = 21, B_G2EMPTY = 27, B_RESFULL = 33,
  B_PTFULL = 34, B_XSFULL = 35, B_CONVDONE = 36, B_G1DONE = 37, B_G2DONE = 38, B_TAILDONE = 39, B_STFULL = 40, B_KDONE = 41, B_F0OK = 42,
  B_KGDONE = 43, B_STAGED = 44, B_STRIP = 45, B_STRIPDONE = 46, B_PTDONE = 47, B_PTSAVED = 48, B_PEERRDY = 49, B_RECV = 50, B_ROLE = 51, B_PUBDONE = 52,
  B_CSL = 57, B_CSDONE = 59, B_PUB3 = 60, B_B97 = 61,
  B_PUB = 53
};
constexpr int bar_log2_count(int i) {
  return (i >= B_WEMPTY && i < B_WEMPTY + 6) || (i >= B_G2EMPTY && i < B_G2EMPTY + 6) || i == B_CONVDONE || i == B_G1DONE || i == B_G2DONE ||
                 i == B_KGDONE || i == B_KDONE || i == B_STRIPDONE || i == B_PTDONE || i == B_PEERRDY
             ? 3
             : ((i >= B_PUB && i < B_PUB + 4) || i == B_STAGED || i == B_B97 ? 2 : (i == B_PUBDONE || i == B_CSDONE || i == B_PUB3 ? 1 : 0));
}
constexpr unsigned long long bar_codes(int base) {
  unsigned long long r = 0;
  for (int i = 0; i < 32; i++) r |= (unsigned long long)bar_log2_count(base + i) << (2 * i);
  return r;
}
constexpr unsigned long long LO_CODES = bar_codes(0), HI_CODES = bar_codes(32);
enum { F_0 = 0, F_CS = 1, F_3 = 2, F_S = 4, F_1 = 8, F_2 = 32, F_COUNT = 224 };

struct Scratch {
  bf16 xT[3][DM * SEQ];
  bf16 h[32 * 24 * 4096];
  uint32_t ptab[DM * PTW];
  float2 stat1[SEQ];
  float2 stat3[SEQ];
  float2 stat2[2][4][SEQ];
  float cs[2 * CSP];
  unsigned flag[F_COUNT * 8];
  unsigned tpc[64];
  unsigned epoch;
};
__device__ __align__(1024) Scratch g_scratch;

#define TS(k)
#define TSA(k)
#define TR(k)
#define TRA(k)
#define TRS(k)

struct Params {
  const bf16 *x0, *logA, *Aim, *Cre, *Cim, *logdt, *Dsk, *wg, *wu, *wd;
  bf16* out;
  Scratch* sc;
};

__device__ __forceinline__ uint32_t smem_u32(const void* p) { return (uint32_t)__cvta_generic_to_shared(p); }
__device__ __forceinline__ void mbar_init(uint32_t a, uint32_t c) { asm volatile("mbarrier.init.shared::cta.b64 [%0], %1;" ::"r"(a), "r"(c) : "memory"); }
__device__ __forceinline__ void mbar_expect(uint32_t a, uint32_t b) { asm volatile("mbarrier.arrive.expect_tx.shared::cta.b64 _, [%0], %1;" ::"r"(a), "r"(b) : "memory"); }
__device__ __forceinline__ void mbar_arrive(uint32_t a) { asm volatile("mbarrier.arrive.shared::cta.b64 _, [%0];" ::"r"(a) : "memory"); }
__device__ __forceinline__ void mbar_wait(uint32_t a, uint32_t par) {
  asm volatile("{\n.reg .pred p;\nLW:\nmbarrier.try_wait.parity.shared::cta.b64 p, [%0], %1;\n@!p bra LW;\n}\n" ::"r"(a), "r"(par) : "memory");
}
__device__ __forceinline__ void mbar_wait_fast(uint32_t a, uint32_t par) { mbar_wait(a, par); }
__device__ __forceinline__ void mbar_wait_checked(uint32_t a, uint32_t par) {
  asm volatile("{\n.reg .pred p;\n.reg .u32 n;\nmov.u32 n, 0;\n"
               "LW:\nmbarrier.try_wait.parity.shared::cta.b64 p, [%0], %1;\n@p bra LD;\n"
               "nanosleep.u32 1000;\nadd.u32 n, n, 1;\nsetp.lt.u32 p, n, %2;\n@p bra LW;\ntrap;\nLD:\n}\n" ::"r"(a), "r"(par), "n"(SPIN_LIMIT) : "memory");
}
__device__ __forceinline__ void flag_wait(const unsigned* f, unsigned target) {
  asm volatile("{\n.reg .pred p;\n.reg .u32 n, v;\nmov.u32 n, 0;\n"
               "LW:\nld.acquire.gpu.global.u32 v, [%0];\nsub.u32 v, v, %1;\nsetp.ge.s32 p, v, 0;\n@p bra LD;\n"
               "add.u32 n, n, 1;\nsetp.lt.u32 p, n, %2;\n@p bra LW;\ntrap;\nLD:\n}\n" ::"l"(f), "r"(target), "n"(SPIN_LIMIT) : "memory");
}
__device__ __forceinline__ bool elect_one() {
  uint32_t r;
  asm volatile("{\n.reg .pred p;\nelect.sync _|p, 0xffffffff;\nselp.u32 %0, 1, 0, p;\n}\n" : "=r"(r));
  return r != 0;
}
__device__ __forceinline__ void flag_publish(unsigned* f) {
  asm volatile("fence.release.gpu;" ::: "memory");
  asm volatile("red.relaxed.gpu.global.add.u32 [%0], 1;" ::"l"(f) : "memory");
}
__device__ __forceinline__ void bar_sync(int id, int n) { asm volatile("bar.sync %0, %1;" ::"r"(id), "r"(n) : "memory"); }
__device__ __forceinline__ void bar_arrive(int id, int n) { asm volatile("bar.arrive %0, %1;" ::"r"(id), "r"(n) : "memory"); }
__device__ __forceinline__ uint32_t peer_addr(uint32_t a, uint32_t rank) { uint32_t r; asm("mapa.shared::cluster.u32 %0, %1, %2;" : "=r"(r) : "r"(a), "r"(rank)); return r; }
__device__ __forceinline__ void mbar_arrive_remote(uint32_t a) { asm volatile("mbarrier.arrive.shared::cluster.b64 _, [%0];" ::"r"(a) : "memory"); }
__device__ __forceinline__ void st_async4(uint32_t a, float x, float y, float z, float w, uint32_t bar) {
  asm volatile("st.async.weak.shared::cluster.mbarrier::complete_tx::bytes.v4.f32 [%0], {%1, %2, %3, %4}, [%5];" ::"r"(a), "f"(x), "f"(y), "f"(z), "f"(w), "r"(bar) : "memory");
}
__device__ __forceinline__ void fence_async_smem() { asm volatile("fence.proxy.async.shared::cta;" ::: "memory"); }
__device__ __forceinline__ void fence_async_all() { asm volatile("fence.proxy.async.global;" ::: "memory"); }
__device__ __forceinline__ void wg_fence() { asm volatile("wgmma.fence.sync.aligned;" ::: "memory"); }
__device__ __forceinline__ void wg_commit() { asm volatile("wgmma.commit_group.sync.aligned;" ::: "memory"); }
template <int N> __device__ __forceinline__ void wg_wait() { asm volatile("wgmma.wait_group.sync.aligned %0;" ::"n"(N) : "memory"); }

__device__ __forceinline__ void bulk_g2s(uint32_t dst, const void* src, uint32_t bytes, uint32_t bar) {
  asm volatile("cp.async.bulk.shared::cluster.global.mbarrier::complete_tx::bytes [%0], [%1], %2, [%3];" ::"r"(dst), "l"(src), "r"(bytes), "r"(bar) : "memory");
}
__device__ __forceinline__ void tma_2d(uint32_t dst, const CUtensorMap* m, int c0, int c1, uint32_t bar) {
  asm volatile("cp.async.bulk.tensor.2d.shared::cluster.global.mbarrier::complete_tx::bytes [%0], [%1, {%2, %3}], [%4];"
               ::"r"(dst), "l"(m), "r"(c0), "r"(c1), "r"(bar) : "memory");
}
__device__ __forceinline__ void tma_4d(uint32_t dst, const CUtensorMap* m, int c0, int c1, int c2, int c3, uint32_t bar) {
  asm volatile("cp.async.bulk.tensor.4d.shared::cluster.global.mbarrier::complete_tx::bytes [%0], [%1, {%2, %3, %4, %5}], [%6];"
               ::"r"(dst), "l"(m), "r"(c0), "r"(c1), "r"(c2), "r"(c3), "r"(bar) : "memory");
}
__device__ __forceinline__ void tma_2d_mc(uint32_t dst, const CUtensorMap* m, int c0, int c1, uint32_t bar) {
  asm volatile("cp.async.bulk.tensor.2d.shared::cluster.global.mbarrier::complete_tx::bytes.multicast::cluster [%0], [%1, {%2, %3}], [%4], %5;"
               ::"r"(dst), "l"(m), "r"(c0), "r"(c1), "r"(bar), "h"((uint16_t)3) : "memory");
}
__device__ __forceinline__ void tma_3d(uint32_t dst, const CUtensorMap* m, int c0, int c1, int c2, uint32_t bar) {
  asm volatile("cp.async.bulk.tensor.3d.shared::cluster.global.mbarrier::complete_tx::bytes [%0], [%1, {%2, %3, %4}], [%5];"
               ::"r"(dst), "l"(m), "r"(c0), "r"(c1), "r"(c2), "r"(bar) : "memory");
}
__device__ __forceinline__ void tma_5d(uint32_t dst, const CUtensorMap* m, int c0, int c1, int c2, int c3, int c4, uint32_t bar) {
  asm volatile("cp.async.bulk.tensor.5d.shared::cluster.global.mbarrier::complete_tx::bytes [%0], [%1, {%2, %3, %4, %5, %6}], [%7];"
               ::"r"(dst), "l"(m), "r"(c0), "r"(c1), "r"(c2), "r"(c3), "r"(c4), "r"(bar) : "memory");
}
__device__ __forceinline__ void tmap_prefetch(const CUtensorMap* m) { asm volatile("prefetch.tensormap [%0];" ::"l"(m) : "memory"); }
__device__ __forceinline__ void l2_prefetch(const void* p, uint32_t bytes) { asm volatile("cp.async.bulk.prefetch.L2.global [%0], %1;" ::"l"(p), "r"(bytes) : "memory"); }

template <class T> __device__ __forceinline__ T* sptr(uint32_t a) { return reinterpret_cast<T*>(__cvta_shared_to_generic(a)); }
__device__ __forceinline__ uint32_t lds32(uint32_t a) { return *sptr<const uint32_t>(a); }
__device__ __forceinline__ float ldsf(uint32_t a) { return *sptr<const float>(a); }
__device__ __forceinline__ float2 ldsf2(uint32_t a) { return *sptr<const float2>(a); }
__device__ __forceinline__ uint4 lds128(uint32_t a) { return *sptr<const uint4>(a); }
__device__ __forceinline__ void sts32(uint32_t a, uint32_t v) { *sptr<uint32_t>(a) = v; }
__device__ __forceinline__ void stsf(uint32_t a, float v) { *sptr<float>(a) = v; }
__device__ __forceinline__ void stsf2(uint32_t a, float x, float y) { *sptr<float2>(a) = make_float2(x, y); }
__device__ __forceinline__ void sts128(uint32_t a, uint4 v) { *sptr<uint4>(a) = v; }
__device__ __forceinline__ void ldsm4t(uint32_t a, uint32_t& r0, uint32_t& r1, uint32_t& r2, uint32_t& r3) {
  asm volatile("ldmatrix.sync.aligned.m8n8.x4.trans.shared.b16 {%0, %1, %2, %3}, [%4];" : "=r"(r0), "=r"(r1), "=r"(r2), "=r"(r3) : "r"(a) : "memory");
}
__device__ __forceinline__ void red_add4(float* p, uint4 v) {
  asm volatile("red.relaxed.gpu.global.add.v4.f32 [%0], {%1, %2, %3, %4};" ::"l"(p), "f"(__uint_as_float(v.x)), "f"(__uint_as_float(v.y)),
               "f"(__uint_as_float(v.z)), "f"(__uint_as_float(v.w)) : "memory");
}
__device__ __forceinline__ void ldsm4(uint32_t a, uint32_t& r0, uint32_t& r1, uint32_t& r2, uint32_t& r3) {
  asm volatile("ldmatrix.sync.aligned.m8n8.x4.shared.b16 {%0, %1, %2, %3}, [%4];" : "=r"(r0), "=r"(r1), "=r"(r2), "=r"(r3) : "r"(a) : "memory");
}
__device__ __forceinline__ void stsm4(uint32_t a, uint32_t r0, uint32_t r1, uint32_t r2, uint32_t r3) {
  asm volatile("stmatrix.sync.aligned.m8n8.x4.shared.b16 [%0], {%1, %2, %3, %4};" ::"r"(a), "r"(r0), "r"(r1), "r"(r2), "r"(r3) : "memory");
}
__device__ __forceinline__ void stsm4t(uint32_t a, uint32_t r0, uint32_t r1, uint32_t r2, uint32_t r3) {
  asm volatile("stmatrix.sync.aligned.m8n8.x4.trans.shared.b16 [%0], {%1, %2, %3, %4};" ::"r"(a), "r"(r0), "r"(r1), "r"(r2), "r"(r3) : "memory");
}
__device__ __forceinline__ uint4 ldg128_cg(const void* p) { uint4 v; asm volatile("ld.global.cg.v4.b32 {%0, %1, %2, %3}, [%4];" : "=r"(v.x), "=r"(v.y), "=r"(v.z), "=r"(v.w) : "l"(p) : "memory"); return v; }
__device__ __forceinline__ uint4 ldg128_nc(const void* p) { uint4 v; asm volatile("ld.global.nc.v4.b32 {%0, %1, %2, %3}, [%4];" : "=r"(v.x), "=r"(v.y), "=r"(v.z), "=r"(v.w) : "l"(p)); return v; }

__device__ __forceinline__ float bf_lo(uint32_t v) { return __uint_as_float(v << 16); }
__device__ __forceinline__ float bf_hi(uint32_t v) { return __uint_as_float(v & 0xffff0000u); }
__device__ __forceinline__ uint32_t pack_bf(float lo, float hi) { uint32_t r; asm("cvt.rn.bf16x2.f32 %0, %1, %2;" : "=r"(r) : "f"(hi), "f"(lo)); return r; }
__device__ __forceinline__ uint32_t pack_h(float lo, float hi) { uint32_t r; asm("cvt.rn.f16x2.f32 %0, %1, %2;" : "=r"(r) : "f"(hi), "f"(lo)); return r; }
__device__ __forceinline__ uint32_t bf2_add(uint32_t a, uint32_t b) { uint32_t r; asm("add.rn.bf16x2 %0, %1, %2;" : "=r"(r) : "r"(a), "r"(b)); return r; }
__device__ __forceinline__ uint32_t bf2_sub(uint32_t a, uint32_t b) { uint32_t r; asm("sub.rn.bf16x2 %0, %1, %2;" : "=r"(r) : "r"(a), "r"(b)); return r; }
__device__ __forceinline__ float bf_round(float x) { return bf_lo(pack_bf(x, 0.f)); }
__device__ __forceinline__ float2 unpack_h(uint32_t v) { return __half22float2(*reinterpret_cast<const __half2*>(&v)); }
__device__ __forceinline__ float ex2f(float x) { float y; asm("ex2.approx.ftz.f32 %0, %1;" : "=f"(y) : "f"(x)); return y; }
__device__ __forceinline__ float rcpf(float x) { float y; asm("rcp.approx.ftz.f32 %0, %1;" : "=f"(y) : "f"(x)); return y; }
__device__ __forceinline__ float bf2f(bf16 v) { return __bfloat162float(v); }

template <int N> __device__ __forceinline__ void pin_regs(float (&a)[N]) {
#pragma unroll
  for (int i = 0; i < N; i++) asm volatile("" : "+f"(a[i])::"memory");
}

__device__ __forceinline__ uint32_t g2_stage_off(uint32_t st) { return st < 2 ? SM_WR + st * G2_STAGE : (st - 2) * G2_STAGE; }
__device__ __forceinline__ uint32_t desc_lo(uint32_t addr, uint32_t lbo) { return ((addr & 0x3FFFF) >> 4) | ((lbo >> 4) << 16); }

__device__ __forceinline__ float2 ln_finalize(float sum, float sq) {
  const float mean = sum * (1.0f / DM);
  const float var = fmaxf(fmaf(-mean, mean, sq * (1.0f / DM)), 0.f);
  const float ve = bf_round(bf_round(var) + 1e-5f);
  float s;
  asm("sqrt.approx.ftz.f32 %0, %1;" : "=f"(s) : "f"(ve));
  return make_float2(bf_round(mean), rcpf(bf_round(s)));
}

__device__ __forceinline__ void wg_g1_n128(float (&d)[64], uint32_t da, uint32_t db, int scale_d) {
  asm volatile("{\n.reg .pred p;\n.reg .b64 da, db;\n.reg .b32 ha, hb;\nsetp.ne.b32 p, %66, 0;\n"
    "mov.b32 ha, 1073741888;\nmov.b32 hb, 1073741888;\nmov.b64 da, {%64, ha};\nmov.b64 db, {%65, hb};\n"
    "wgmma.mma_async.sync.aligned.m64n128k16.f32.bf16.bf16 "
    "{%0, %1, %2, %3, %4, %5, %6, %7, %8, %9, %10, %11, %12, %13, %14, %15, %16, %17, %18, %19, %20, %21, %22, %23, %24, %25, %26, %27, %28, %29, %30, %31, %32, %33, %34, %35, %36, %37, %38, %39, %40, %41, %42, %43, %44, %45, %46, %47, %48, %49, %50, %51, %52, %53, %54, %55, %56, %57, %58, %59, %60, %61, %62, %63}, "
    "da, db, p, 1, 1, 1, 1;\n}\n"
    : "+f"(d[0]), "+f"(d[1]), "+f"(d[2]), "+f"(d[3]), "+f"(d[4]), "+f"(d[5]), "+f"(d[6]), "+f"(d[7]), "+f"(d[8]), "+f"(d[9]), "+f"(d[10]), "+f"(d[11]), "+f"(d[12]), "+f"(d[13]), "+f"(d[14]), "+f"(d[15]), "+f"(d[16]), "+f"(d[17]), "+f"(d[18]), "+f"(d[19]), "+f"(d[20]), "+f"(d[21]), "+f"(d[22]), "+f"(d[23]), "+f"(d[24]), "+f"(d[25]), "+f"(d[26]), "+f"(d[27]), "+f"(d[28]), "+f"(d[29]), "+f"(d[30]), "+f"(d[31]), "+f"(d[32]), "+f"(d[33]), "+f"(d[34]), "+f"(d[35]), "+f"(d[36]), "+f"(d[37]), "+f"(d[38]), "+f"(d[39]), "+f"(d[40]), "+f"(d[41]), "+f"(d[42]), "+f"(d[43]), "+f"(d[44]), "+f"(d[45]), "+f"(d[46]), "+f"(d[47]), "+f"(d[48]), "+f"(d[49]), "+f"(d[50]), "+f"(d[51]), "+f"(d[52]), "+f"(d[53]), "+f"(d[54]), "+f"(d[55]), "+f"(d[56]), "+f"(d[57]), "+f"(d[58]), "+f"(d[59]), "+f"(d[60]), "+f"(d[61]), "+f"(d[62]), "+f"(d[63])
    : "r"(da), "r"(db), "r"(scale_d));
}
__device__ __forceinline__ void wg_g1_n112(float (&d)[64], uint32_t da, uint32_t db, int scale_d) {
  asm volatile("{\n.reg .pred p;\n.reg .b64 da, db;\n.reg .b32 ha, hb;\nsetp.ne.b32 p, %58, 0;\n"
    "mov.b32 ha, 1073741888;\nmov.b32 hb, 1073741888;\nmov.b64 da, {%56, ha};\nmov.b64 db, {%57, hb};\n"
    "wgmma.mma_async.sync.aligned.m64n112k16.f32.bf16.bf16 "
    "{%0, %1, %2, %3, %4, %5, %6, %7, %8, %9, %10, %11, %12, %13, %14, %15, %16, %17, %18, %19, %20, %21, %22, %23, %24, %25, %26, %27, %28, %29, %30, %31, %32, %33, %34, %35, %36, %37, %38, %39, %40, %41, %42, %43, %44, %45, %46, %47, %48, %49, %50, %51, %52, %53, %54, %55}, "
    "da, db, p, 1, 1, 1, 1;\n}\n"
    : "+f"(d[0]), "+f"(d[1]), "+f"(d[2]), "+f"(d[3]), "+f"(d[4]), "+f"(d[5]), "+f"(d[6]), "+f"(d[7]), "+f"(d[8]), "+f"(d[9]), "+f"(d[10]), "+f"(d[11]), "+f"(d[12]), "+f"(d[13]), "+f"(d[14]), "+f"(d[15]), "+f"(d[16]), "+f"(d[17]), "+f"(d[18]), "+f"(d[19]), "+f"(d[20]), "+f"(d[21]), "+f"(d[22]), "+f"(d[23]), "+f"(d[24]), "+f"(d[25]), "+f"(d[26]), "+f"(d[27]), "+f"(d[28]), "+f"(d[29]), "+f"(d[30]), "+f"(d[31]), "+f"(d[32]), "+f"(d[33]), "+f"(d[34]), "+f"(d[35]), "+f"(d[36]), "+f"(d[37]), "+f"(d[38]), "+f"(d[39]), "+f"(d[40]), "+f"(d[41]), "+f"(d[42]), "+f"(d[43]), "+f"(d[44]), "+f"(d[45]), "+f"(d[46]), "+f"(d[47]), "+f"(d[48]), "+f"(d[49]), "+f"(d[50]), "+f"(d[51]), "+f"(d[52]), "+f"(d[53]), "+f"(d[54]), "+f"(d[55])
    : "r"(da), "r"(db), "r"(scale_d));
}
__device__ __forceinline__ void wg_g2_n64(float (&d)[32], uint32_t da, uint32_t db, int scale_d) {
  asm volatile("{\n.reg .pred p;\n.reg .b64 da, db;\n.reg .b32 ha, hb;\nsetp.ne.b32 p, %34, 0;\n"
    "mov.b32 ha, 1073741888;\nmov.b32 hb, 8;\nmov.b64 da, {%32, ha};\nmov.b64 db, {%33, hb};\n"
    "wgmma.mma_async.sync.aligned.m64n64k16.f32.bf16.bf16 "
    "{%0, %1, %2, %3, %4, %5, %6, %7, %8, %9, %10, %11, %12, %13, %14, %15, %16, %17, %18, %19, %20, %21, %22, %23, %24, %25, %26, %27, %28, %29, %30, %31}, "
    "da, db, p, 1, 1, 1, 0;\n}\n"
    : "+f"(d[0]), "+f"(d[1]), "+f"(d[2]), "+f"(d[3]), "+f"(d[4]), "+f"(d[5]), "+f"(d[6]), "+f"(d[7]), "+f"(d[8]), "+f"(d[9]), "+f"(d[10]), "+f"(d[11]), "+f"(d[12]), "+f"(d[13]), "+f"(d[14]), "+f"(d[15]), "+f"(d[16]), "+f"(d[17]), "+f"(d[18]), "+f"(d[19]), "+f"(d[20]), "+f"(d[21]), "+f"(d[22]), "+f"(d[23]), "+f"(d[24]), "+f"(d[25]), "+f"(d[26]), "+f"(d[27]), "+f"(d[28]), "+f"(d[29]), "+f"(d[30]), "+f"(d[31])
    : "r"(da), "r"(db), "r"(scale_d));
}
__device__ __forceinline__ void wg_g2_n128(float (&d)[64], uint32_t da, uint32_t db, int scale_d) {
  asm volatile("{\n.reg .pred p;\n.reg .b64 da, db;\n.reg .b32 ha, hb;\nsetp.ne.b32 p, %66, 0;\n"
    "mov.b32 ha, 1073741888;\nmov.b32 hb, 8;\nmov.b64 da, {%64, ha};\nmov.b64 db, {%65, hb};\n"
    "wgmma.mma_async.sync.aligned.m64n128k16.f32.bf16.bf16 "
    "{%0, %1, %2, %3, %4, %5, %6, %7, %8, %9, %10, %11, %12, %13, %14, %15, %16, %17, %18, %19, %20, %21, %22, %23, %24, %25, %26, %27, %28, %29, %30, %31, %32, %33, %34, %35, %36, %37, %38, %39, %40, %41, %42, %43, %44, %45, %46, %47, %48, %49, %50, %51, %52, %53, %54, %55, %56, %57, %58, %59, %60, %61, %62, %63}, "
    "da, db, p, 1, 1, 1, 0;\n}\n"
    : "+f"(d[0]), "+f"(d[1]), "+f"(d[2]), "+f"(d[3]), "+f"(d[4]), "+f"(d[5]), "+f"(d[6]), "+f"(d[7]), "+f"(d[8]), "+f"(d[9]), "+f"(d[10]), "+f"(d[11]), "+f"(d[12]), "+f"(d[13]), "+f"(d[14]), "+f"(d[15]), "+f"(d[16]), "+f"(d[17]), "+f"(d[18]), "+f"(d[19]), "+f"(d[20]), "+f"(d[21]), "+f"(d[22]), "+f"(d[23]), "+f"(d[24]), "+f"(d[25]), "+f"(d[26]), "+f"(d[27]), "+f"(d[28]), "+f"(d[29]), "+f"(d[30]), "+f"(d[31]), "+f"(d[32]), "+f"(d[33]), "+f"(d[34]), "+f"(d[35]), "+f"(d[36]), "+f"(d[37]), "+f"(d[38]), "+f"(d[39]), "+f"(d[40]), "+f"(d[41]), "+f"(d[42]), "+f"(d[43]), "+f"(d[44]), "+f"(d[45]), "+f"(d[46]), "+f"(d[47]), "+f"(d[48]), "+f"(d[49]), "+f"(d[50]), "+f"(d[51]), "+f"(d[52]), "+f"(d[53]), "+f"(d[54]), "+f"(d[55]), "+f"(d[56]), "+f"(d[57]), "+f"(d[58]), "+f"(d[59]), "+f"(d[60]), "+f"(d[61]), "+f"(d[62]), "+f"(d[63])
    : "r"(da), "r"(db), "r"(scale_d));
}
__device__ __forceinline__ void wg_kg_n32(float (&d)[16], uint32_t da, uint32_t db, int scale_d) {
  asm volatile("{\n.reg .pred p;\n.reg .b64 da, db;\n.reg .b32 ha, hb;\nsetp.ne.b32 p, %18, 0;\n"
    "mov.b32 ha, 1073741888;\nmov.b32 hb, 1073741888;\nmov.b64 da, {%16, ha};\nmov.b64 db, {%17, hb};\n"
    "wgmma.mma_async.sync.aligned.m64n32k16.f32.f16.f16 "
    "{%0, %1, %2, %3, %4, %5, %6, %7, %8, %9, %10, %11, %12, %13, %14, %15}, "
    "da, db, p, 1, 1, 0, 0;\n}\n"
    : "+f"(d[0]), "+f"(d[1]), "+f"(d[2]), "+f"(d[3]), "+f"(d[4]), "+f"(d[5]), "+f"(d[6]), "+f"(d[7]), "+f"(d[8]), "+f"(d[9]), "+f"(d[10]), "+f"(d[11]), "+f"(d[12]), "+f"(d[13]), "+f"(d[14]), "+f"(d[15])
    : "r"(da), "r"(db), "r"(scale_d));
}
__device__ __forceinline__ void wg_cv_n64(float (&d)[32], uint32_t a0, uint32_t a1, uint32_t a2, uint32_t a3, uint32_t db, int scale_d) {
  asm volatile("{\n.reg .pred p;\n.reg .b64 db;\n.reg .b32 hb;\nsetp.ne.b32 p, %37, 0;\n"
    "mov.b32 hb, 2147483680;\nmov.b64 db, {%36, hb};\n"
    "wgmma.mma_async.sync.aligned.m64n64k16.f32.f16.f16 "
    "{%0, %1, %2, %3, %4, %5, %6, %7, %8, %9, %10, %11, %12, %13, %14, %15, %16, %17, %18, %19, %20, %21, %22, %23, %24, %25, %26, %27, %28, %29, %30, %31}, "
    "{%32, %33, %34, %35}, db, p, 1, 1, 0;\n}\n"
    : "+f"(d[0]), "+f"(d[1]), "+f"(d[2]), "+f"(d[3]), "+f"(d[4]), "+f"(d[5]), "+f"(d[6]), "+f"(d[7]), "+f"(d[8]), "+f"(d[9]), "+f"(d[10]), "+f"(d[11]), "+f"(d[12]), "+f"(d[13]), "+f"(d[14]), "+f"(d[15]), "+f"(d[16]), "+f"(d[17]), "+f"(d[18]), "+f"(d[19]), "+f"(d[20]), "+f"(d[21]), "+f"(d[22]), "+f"(d[23]), "+f"(d[24]), "+f"(d[25]), "+f"(d[26]), "+f"(d[27]), "+f"(d[28]), "+f"(d[29]), "+f"(d[30]), "+f"(d[31])
    : "r"(a0), "r"(a1), "r"(a2), "r"(a3), "r"(db), "r"(scale_d));
}
__device__ __forceinline__ void wg_cv_n56(float (&d)[28], uint32_t a0, uint32_t a1, uint32_t a2, uint32_t a3, uint32_t db, int scale_d) {
  asm volatile("{\n.reg .pred p;\n.reg .b64 db;\n.reg .b32 hb;\nsetp.ne.b32 p, %33, 0;\n"
    "mov.b32 hb, 2147483680;\nmov.b64 db, {%32, hb};\n"
    "wgmma.mma_async.sync.aligned.m64n56k16.f32.f16.f16 "
    "{%0, %1, %2, %3, %4, %5, %6, %7, %8, %9, %10, %11, %12, %13, %14, %15, %16, %17, %18, %19, %20, %21, %22, %23, %24, %25, %26, %27}, "
    "{%28, %29, %30, %31}, db, p, 1, 1, 0;\n}\n"
    : "+f"(d[0]), "+f"(d[1]), "+f"(d[2]), "+f"(d[3]), "+f"(d[4]), "+f"(d[5]), "+f"(d[6]), "+f"(d[7]), "+f"(d[8]), "+f"(d[9]), "+f"(d[10]), "+f"(d[11]), "+f"(d[12]), "+f"(d[13]), "+f"(d[14]), "+f"(d[15]), "+f"(d[16]), "+f"(d[17]), "+f"(d[18]), "+f"(d[19]), "+f"(d[20]), "+f"(d[21]), "+f"(d[22]), "+f"(d[23]), "+f"(d[24]), "+f"(d[25]), "+f"(d[26]), "+f"(d[27])
    : "r"(a0), "r"(a1), "r"(a2), "r"(a3), "r"(db), "r"(scale_d));
}
__device__ __forceinline__ void wg_cv_n40(float (&d)[20], uint32_t a0, uint32_t a1, uint32_t a2, uint32_t a3, uint32_t db, int scale_d) {
  asm volatile("{\n.reg .pred p;\n.reg .b64 db;\n.reg .b32 hb;\nsetp.ne.b32 p, %25, 0;\n"
    "mov.b32 hb, 2147483680;\nmov.b64 db, {%24, hb};\n"
    "wgmma.mma_async.sync.aligned.m64n40k16.f32.f16.f16 "
    "{%0, %1, %2, %3, %4, %5, %6, %7, %8, %9, %10, %11, %12, %13, %14, %15, %16, %17, %18, %19}, "
    "{%20, %21, %22, %23}, db, p, 1, 1, 0;\n}\n"
    : "+f"(d[0]), "+f"(d[1]), "+f"(d[2]), "+f"(d[3]), "+f"(d[4]), "+f"(d[5]), "+f"(d[6]), "+f"(d[7]), "+f"(d[8]), "+f"(d[9]), "+f"(d[10]), "+f"(d[11]), "+f"(d[12]), "+f"(d[13]), "+f"(d[14]), "+f"(d[15]), "+f"(d[16]), "+f"(d[17]), "+f"(d[18]), "+f"(d[19])
    : "r"(a0), "r"(a1), "r"(a2), "r"(a3), "r"(db), "r"(scale_d));
}
__device__ __forceinline__ void wg_cv_n16t(float (&d)[8], uint32_t a0, uint32_t a1, uint32_t a2, uint32_t a3, uint32_t db, int scale_d) {
  asm volatile("{\n.reg .pred p;\n.reg .b64 db;\n.reg .b32 hb;\nsetp.ne.b32 p, %13, 0;\n"
    "mov.b32 hb, 3221225488;\nmov.b64 db, {%12, hb};\n"
    "wgmma.mma_async.sync.aligned.m64n16k16.f32.f16.f16 "
    "{%0, %1, %2, %3, %4, %5, %6, %7}, "
    "{%8, %9, %10, %11}, db, p, 1, 1, 1;\n}\n"
    : "+f"(d[0]), "+f"(d[1]), "+f"(d[2]), "+f"(d[3]), "+f"(d[4]), "+f"(d[5]), "+f"(d[6]), "+f"(d[7])
    : "r"(a0), "r"(a1), "r"(a2), "r"(a3), "r"(db), "r"(scale_d));
}

#define G2_HOLD 12
__device__ __forceinline__ float2 cmul(float2 a, float2 b) {
  return make_float2(fmaf(a.x, b.x, -a.y * b.y), fmaf(a.x, b.y, a.y * b.x));
}
__device__ __forceinline__ float2 cexp_p(float ar, float ai, float p) {
  float xr = ar * p, xi = ai * p;
  float mag = ex2f(xr * 1.4426950408889634f);
  float k = rintf(xi * 0.15915494309189535f);
  float r = fmaf(-k, 6.2831854820251465f, xi);
  r = fmaf(-k, -1.7484555314695172e-07f, r);
  float s, c;
  __sincosf(r, &s, &c);
  return make_float2(mag * c, mag * s);
}
__device__ __forceinline__ int pos_index(int j) {
  int b = (int)(pack_bf((float)j, 0.f) & 0xffffu) - 17024;
  return j < 128 ? j : b;
}

struct KParam { float logA, aim, cre, cim, logdt; };

__device__ __forceinline__ void kgen(uint32_t sb, int w, int wp, int lane, const KParam (&kp)[2], float (&kinv)[2]) {
  const int t = wp * 32 + lane;
  float ar[2], ai[2];
  float2 C[2];
  const uint32_t mxa = sb + SM_MISC + 12288 + w * 32;
#pragma unroll
  for (int v = 0; v < 2; v++) {
    const float dt = bf_round(expf(kp[v].logdt));
    const float lar = -bf_round(expf(kp[v].logA));
    ar[v] = lar * dt; ai[v] = kp[v].aim * dt;
    C[v] = make_float2(kp[v].cre * dt, kp[v].cim * dt);
    float mx = fmaxf(fabsf(C[v].x), fabsf(C[v].y));
#pragma unroll
    for (int o = 16; o; o >>= 1) mx = fmaxf(mx, __shfl_xor_sync(0xffffffffu, mx, o));
    if (lane == 0) stsf(mxa + v * 16 + wp * 4, mx);
  }
  bar_sync(1 + w, 128);
#pragma unroll
  for (int v = 0; v < 2; v++) {
    const uint4 m4 = lds128(mxa + v * 16);
    const float mx = fmaxf(fmaxf(__uint_as_float(m4.x), __uint_as_float(m4.y)), fmaxf(__uint_as_float(m4.z), __uint_as_float(m4.w)));
    int e = (__float_as_uint(mx) >> 23) & 255;
    e = min(max(e, 4), 254);
    const float scale2 = __uint_as_float((uint32_t)(258 - e) << 23);
    kinv[v] = __uint_as_float((uint32_t)(e - 3) << 23);
    C[v].x *= scale2; C[v].y *= scale2;
  }
  const uint32_t ga = sb + KG_A + w * 28672 + wp * 3072 + lane * 4;
  const uint32_t fa = sb + KG_B + w * 28672 + wp * 4096 + lane * 4;
  auto putG = [&](int v, int h, float2 g) { sts32(((ga + v * 57344) ^ ((h & 7) << 4)) + h * 128, pack_h(g.x, -g.y)); };
  float2 E8[2];
#pragma unroll
  for (int v = 0; v < 2; v++) {
    const float2 E1 = cexp_p(ar[v], ai[v], 1.f), E256 = cexp_p(ar[v], ai[v], 256.f);
    const float2 E2 = cmul(E1, E1), E4 = cmul(E2, E2), E512 = cmul(E256, E256), E1024 = cmul(E512, E512);
    E8[v] = cmul(E4, E4);
    {
      float2 g0 = C[v], g1 = cmul(C[v], E1);
      putG(v, 0, g0); putG(v, 1, g1);
#pragma unroll
      for (int h = 2; h < 8; h += 2) { g0 = cmul(g0, E2); g1 = cmul(g1, E2); putG(v, h, g0); putG(v, h + 1, g1); }
    }
    {
      const float2 g = cmul(C[v], E256), g4 = cmul(g, E4);
      putG(v, 8, g); putG(v, 9, cmul(g, E2)); putG(v, 10, g4); putG(v, 11, cmul(g4, E2));
    }
    {
      const float2 g = cmul(C[v], E512), g2 = cmul(g, E256);
      putG(v, 12, g); putG(v, 13, cmul(g, E4)); putG(v, 14, g2); putG(v, 15, cmul(g2, E4));
    }
    {
      const float2 g = cmul(C[v], E1024), g2 = cmul(g, E512);
      putG(v, 16, g); putG(v, 17, cmul(g, E256)); putG(v, 18, g2); putG(v, 19, cmul(g2, E256)); putG(v, 20, cmul(g, E1024));
    }
  }
  {
    float2 f[2][2], E16[2];
#pragma unroll
    for (int v = 0; v < 2; v++) { E16[v] = cmul(E8[v], E8[v]); f[v][0] = make_float2(1.f, 0.f); f[v][1] = E8[v]; }
#pragma unroll 2
    for (int o = 0; o < 32; o += 2) {
      const uint32_t a0 = (fa ^ ((o & 7) << 4)) + o * 128, a1 = (fa ^ (((o + 1) & 7) << 4)) + (o + 1) * 128;
#pragma unroll
      for (int v = 0; v < 2; v++) {
        sts32(a0 + v * 57344, pack_h(f[v][0].x, f[v][0].y));
        sts32(a1 + v * 57344, pack_h(f[v][1].x, f[v][1].y));
        f[v][0] = cmul(f[v][0], E16[v]); f[v][1] = cmul(f[v][1], E16[v]);
      }
    }
  }
  TS(37);
  fence_async_smem();
  bar_sync(1 + w, 128);
  float acc0[16], acc1[16];
#pragma unroll
  for (int i = 0; i < 16; i++) { acc0[i] = 0.f; acc1[i] = 0.f; }
  pin_regs(acc0); pin_regs(acc1);
  {
    const uint32_t da = desc_lo(sb + KG_A + w * 28672, 16), db = desc_lo(sb + KG_B + w * 28672, 16);
    wg_fence();
#pragma unroll 1
    for (int kb = 0; kb < 4; kb++) {
#pragma unroll
      for (int k = 0; k < 4; k++) {
        wg_kg_n32(acc0, da + kb * 192 + k * 2, db + kb * 256 + k * 2, (kb | k) != 0);
        wg_kg_n32(acc1, da + 3584 + kb * 192 + k * 2, db + 3584 + kb * 256 + k * 2, (kb | k) != 0);
      }
    }
    wg_commit();
    wg_wait<0>();
    pin_regs(acc0); pin_regs(acc1);
    if (lane == 0) mbar_arrive(sb + SM_BAR + 8 * B_KGDONE);
  }
  const uint32_t kt = sb + SM_MISC + w * 2592;
  {
    const int g = lane >> 2, c = lane & 3;
    if (wp == 0) {
      const int b2 = g < 4 ? 256 + g : 384 + 64 * ((g - 4) >> 1) + (g & 1), s2 = g < 4 ? 4 : 2;
      const uint32_t k0 = kt + (g + 16 * c) * 4, k1 = kt + (b2 + s2 * 2 * c) * 4;
#pragma unroll
      for (int nb = 0; nb < 4; nb++)
#pragma unroll
        for (int k = 0; k < 2; k++) {
          const int o = 8 * nb + k;
          stsf(k0 + 32 * o, acc0[4 * nb + k]); stsf(k0 + 32 * o + 5184, acc1[4 * nb + k]);
          stsf(k1 + s2 * 4 * o, acc0[4 * nb + 2 + k]); stsf(k1 + s2 * 4 * o + 5184, acc1[4 * nb + 2 + k]);
        }
    } else if (wp == 1) {
      if (g < 4) {
        const uint32_t k0 = kt + (512 + 32 * g + 2 * c) * 4;
#pragma unroll
        for (int nb = 0; nb < 4; nb++) { stsf2(k0 + 32 * nb, acc0[4 * nb], acc0[4 * nb + 1]); stsf2(k0 + 32 * nb + 5184, acc1[4 * nb], acc1[4 * nb + 1]); }
      } else if (g == 4 && c == 0) {
        stsf(kt + 640 * 4, acc0[0]); stsf(kt + 640 * 4 + 5184, acc1[0]);
      }
    }
  }
  bar_sync(1 + w, 128);
  const uint32_t pt = sb + SM_PT + w * (PTW * 4);
#pragma unroll 1
  for (int i = 0; i < 3; i++) {
    const int q = t + 128 * i;
    if (q < PAW / 4) {
      const int x0 = 4 * q - 65;
      float kv[2][5];
#pragma unroll
      for (int k = 0; k < 5; k++) {
        const int x = x0 + k;
        const bool ok = x >= 0 && x <= 1028;
        const uint32_t a = kt + (ok ? pos_index(x) : 0) * 4;
#pragma unroll
        for (int v = 0; v < 2; v++) { const float f = ldsf(a + v * 5184); kv[v][k] = ok ? f : 0.f; }
      }
#pragma unroll
      for (int v = 0; v < 2; v++)
        sts128(pt + v * (2 * PTW * 4) + q * 16, make_uint4(pack_h(kv[v][1], kv[v][0]), pack_h(kv[v][2], kv[v][1]), pack_h(kv[v][3], kv[v][2]), pack_h(kv[v][4], kv[v][3])));
    }
  }
  {
    const int z = t - 64;
#pragma unroll
    for (int v = 0; v < 2; v++) {
      const uint32_t k0 = kt + v * 5184 + 8 * max(z, 0);
      const float a = ldsf(k0 + 511 * 4), b = ldsf(k0 + 512 * 4), c = ldsf(k0 + 513 * 4), d = ldsf(k0 + 514 * 4);
      sts32(pt + v * (2 * PTW * 4) + (PAW + t) * 4, pack_h(z >= 0 ? d : 0.f, z >= 1 ? b : 0.f));
      sts32(pt + v * (2 * PTW * 4) + (PAW + 128 + t) * 4, pack_h(z >= 0 ? c : 0.f, z >= 1 ? a : 0.f));
    }
  }
  fence_async_smem();
  __syncwarp();
  if (lane == 0) mbar_arrive(sb + SM_BAR + 8 * B_PTDONE);
}

__device__ __forceinline__ void strip_transpose(uint32_t sb, int warp, int lane, int cta) {
  mbar_wait(sb + SM_BAR + 8 * B_STRIP, 0);
  TS(17);
  const int g = lane >> 2, c = lane & 3;
  const bool mine = (g >> 2) == (cta & 1);
  const uint32_t dst = sb + CV_XS + (g & 3) * 4096 + c * 4 + warp * 512;
  uint32_t r[8][4];
#pragma unroll
  for (int i = 0; i < 8; i++) ldsm4t(sb + SM_STRIP + ((warp * 8 + i) * 32 + lane) * 16, r[i][0], r[i][1], r[i][2], r[i][3]);
  if (mine) {
#pragma unroll
    for (int i = 0; i < 8; i++)
#pragma unroll
      for (int k = 0; k < 4; k++) sts32(dst + i * 64 + k * 16, r[i][k]);
  }
  fence_async_smem();
  __syncwarp();
  if (lane == 0) mbar_arrive(sb + SM_BAR + 8 * B_STRIPDONE);
}

__device__ __forceinline__ void load_mu2(uint32_t (&q)[16], uint32_t a) {
#pragma unroll
  for (int h = 0; h < 2; h++) {
    q[8 * h + 2] = lds32(a + h * 256); q[8 * h] = lds32(a + h * 256 + 32); q[8 * h + 1] = lds32(a + h * 256 + 64);
    q[8 * h + 4] = lds32(a + h * 256 + 96); q[8 * h + 5] = lds32(a + h * 256 + 128);
  }
}
__device__ __forceinline__ void fix_mu(uint32_t (&q)[16], int h) { q[8 * h + 3] = q[8 * h]; q[8 * h + 6] = q[8 * h + 1]; q[8 * h + 7] = q[8 * h + 4]; }
#define MU2_GROUP(FN, ACC, Q, DB, SC0)                        \
  do {                                                        \
    fix_mu(Q, 0); fix_mu(Q, 1);                               \
    wg_fence();                                               \
    FN(ACC, Q[0], Q[1], Q[2], Q[3], (DB) + 2, SC0);           \
    FN(ACC, Q[4], Q[5], Q[6], Q[7], (DB), 1);                 \
    FN(ACC, Q[8], Q[9], Q[10], Q[11], (DB) - 8 + 2, 1);       \
    FN(ACC, Q[12], Q[13], Q[14], Q[15], (DB) - 8, 1);         \
    wg_commit();                                              \
  } while (0)
__device__ __forceinline__ void load_far(uint32_t (&q)[16], uint32_t a) {
  q[2] = lds32(a);
#pragma unroll
  for (int k = 0; k < 4; k++) { q[4 * k] = lds32(a + (2 * k + 1) * 32); q[4 * k + 1] = lds32(a + (2 * k + 2) * 32); }
}
#define FAR_GROUP(ACC, Q, DB, SC0)                                                        \
  do {                                                                                    \
    _Pragma("unroll") for (int k = 0; k < 4; k++) { Q[4 * k + 3] = Q[4 * k]; if (k) Q[4 * k + 2] = Q[4 * k - 3]; } \
    wg_fence();                                                                           \
    wg_cv_n16t(ACC, Q[0], Q[1], Q[2], Q[3], (DB) + 96, SC0);                              \
    wg_cv_n16t(ACC, Q[4], Q[5], Q[6], Q[7], (DB) + 64, 1);                                \
    wg_cv_n16t(ACC, Q[8], Q[9], Q[10], Q[11], (DB) + 32, 1);                              \
    wg_cv_n16t(ACC, Q[12], Q[13], Q[14], Q[15], (DB), 1);                                 \
    wg_commit();                                                                          \
  } while (0)

__device__ __forceinline__ uint32_t u_chunk(uint32_t base, int q) {
  const int qq = q + 64, row = qq >> 2;
  return base + row * 64 + (((qq & 3) ^ ((row >> 1) & 3)) << 4);
}

__device__ __forceinline__ void conv_phase(const Params& p, uint32_t sb, int layer, int w, int wp, int lane, int cta,
                                           float kinvA, float kinvB) {
  const int t = wp * 32 + lane, T = w * 128 + t;
  const uint32_t bar = sb + SM_BAR;
  if (layer == 0) bar_sync(4, 256);
  sts128(sb + CV_U + (w + 2 * (t >> 6)) * 5120 + (t & 63) * 16, make_uint4(0, 0, 0, 0));
  mbar_wait(bar + 8 * B_XSFULL, layer);
  TS(3 + 20 * layer);
  {
    uint4 v[4];
#pragma unroll
    for (int i = 0; i < 4; i++) v[i] = lds128(sb + CV_B97 + T * 64 + i * 16);
    const uint32_t sa = sb + SM_STAT + (T >> 1) * 16 + (T & 1) * 8192;
#pragma unroll
    for (int i = 0; i < 4; i++) {
      const float2 a = ln_finalize(__uint_as_float(v[i].x), __uint_as_float(v[i].y));
      const float2 b = ln_finalize(__uint_as_float(v[i].z), __uint_as_float(v[i].w));
      sts128(sa + i * 2048, make_uint4(__byte_perm(__float_as_uint(a.x), __float_as_uint(b.x), 0x7632), __float_as_uint(a.y), __float_as_uint(b.y), 0));
    }
    bar_sync(4, 256);
  }
  {
    uint4 st[8], x[4];
#pragma unroll
    for (int i = 0; i < 8; i++) st[i] = lds128(sb + SM_STAT + t * 16 + i * 2048);
#pragma unroll
    for (int i = 0; i < 4; i++) x[i] = lds128(sb + CV_XS + (w + 2 * (i >> 1)) * 4096 + t * 32 + (i & 1) * 16);
#pragma unroll
    for (int i = 0; i < 4; i++) {
      const uint32_t xx[4] = {x[i].x, x[i].y, x[i].z, x[i].w};
      uint32_t hh[4];
#pragma unroll
      for (int k = 0; k < 4; k++) {
        const uint4 s4 = st[4 * (i & 1) + k];
        const uint32_t dd = bf2_sub(xx[k], s4.x);
        hh[k] = pack_h(bf_lo(dd) * __uint_as_float(s4.y), bf_hi(dd) * __uint_as_float(s4.z));
      }
      sts128(u_chunk(sb + CV_U + (w + 2 * (i >> 1)) * 5120, 2 * t + (i & 1)), make_uint4(hh[0], hh[1], hh[2], hh[3]));
    }
  }
  fence_async_smem();
  bar_sync(4, 256);
  if (w == 1) {
#pragma unroll 1
    for (int h2 = 0; h2 < 2; h2++) {
      uint4 x[8];
#pragma unroll
      for (int k = 0; k < 8; k++) x[k] = lds128(u_chunk(sb + CV_U + (2 * h2 + (k >> 2)) * 5120, t - 3 + (k & 3)));
#pragma unroll
      for (int v = 0; v < 2; v++) {
        float u[32];
#pragma unroll
        for (int k = 0; k < 4; k++) {
          float2 f;
          f = unpack_h(x[4 * v + k].x); u[8 * k] = f.x; u[8 * k + 1] = f.y;
          f = unpack_h(x[4 * v + k].y); u[8 * k + 2] = f.x; u[8 * k + 3] = f.y;
          f = unpack_h(x[4 * v + k].z); u[8 * k + 4] = f.x; u[8 * k + 5] = f.y;
          f = unpack_h(x[4 * v + k].w); u[8 * k + 6] = f.x; u[8 * k + 7] = f.y;
        }
        float s9[8], s7[8];
        s9[0] = ((u[4] + u[5]) + (u[6] + u[7])) + ((u[8] + u[9]) + (u[10] + u[11])) + u[12];
        s9[4] = ((u[8] + u[9]) + (u[10] + u[11])) + ((u[12] + u[13]) + (u[14] + u[15])) + u[16];
        s7[0] = ((u[13] + u[14]) + (u[15] + u[16])) + ((u[17] + u[18]) + u[19]);
        s7[4] = ((u[17] + u[18]) + (u[19] + u[20])) + ((u[21] + u[22]) + u[23]);
#pragma unroll
        for (int j = 1; j < 4; j++) {
          s9[j] = s9[j - 1] + (u[j + 12] - u[j + 3]); s9[j + 4] = s9[j + 3] + (u[j + 16] - u[j + 7]);
          s7[j] = s7[j - 1] + (u[j + 19] - u[j + 12]); s7[j + 4] = s7[j + 3] + (u[j + 23] - u[j + 16]);
        }
        const uint32_t off = (uint32_t)(t * 16) ^ (((t >> 3) & 1) << 4);
        const uint32_t ba = sb + CV_B97 + (2 * h2 + v) * 4096 + off;
        sts128(ba, make_uint4(pack_h(s9[0], s9[1]), pack_h(s9[2], s9[3]), pack_h(s9[4], s9[5]), pack_h(s9[6], s9[7])));
        sts128(ba + 2048, make_uint4(pack_h(s7[0], s7[1]), pack_h(s7[2], s7[3]), pack_h(s7[4], s7[5]), pack_h(s7[6], s7[7])));
      }
    }
    fence_async_smem();
    __syncwarp();
    if (lane == 0) mbar_arrive(bar + 8 * B_B97);
  }
  if (layer != 0) mbar_wait(bar + 8 * B_PTFULL, 0);
  TS(4 + 20 * layer);

  const int g = lane >> 2, c = lane & 3;
  bf16* xout = p.sc->xT[layer == 0 ? 0 : 2];
  const uint32_t ex = sb + (w ? CV_E0 : CV_E1), y3 = ex + 8192;
  float ps[16], pq[16];
#pragma unroll
  for (int i = 0; i < 16; i++) { ps[i] = 0.f; pq[i] = 0.f; }
#pragma unroll 1
  for (int v = 0; v < 2; v++) {
    const int slot = w + 2 * v, ch = 4 * cta + slot;
    const float dsk = bf2f(p.Dsk[ch]);
    const uint32_t pa = sb + SM_PT + slot * (PTW * 4) + (64 + 16 * wp + g - 2 * c) * 4;
    const uint32_t ub = sb + CV_U + slot * 5120;
    const uint32_t du = desc_lo(ub + 16 * 64, 16);
    const uint32_t d9 = desc_lo(sb + CV_B97 + slot * 4096, 2048);
    float acc1[32], acc2[28], acc4[20], acc3[8];
#pragma unroll
    for (int i = 0; i < 32; i++) acc1[i] = 0.f;
#pragma unroll
    for (int i = 0; i < 28; i++) acc2[i] = 0.f;
#pragma unroll
    for (int i = 0; i < 20; i++) acc4[i] = 0.f;
#pragma unroll
    for (int i = 0; i < 8; i++) acc3[i] = 0.f;
    pin_regs(acc1); pin_regs(acc2); pin_regs(acc4); pin_regs(acc3);
    uint32_t qa[16], qb[16], qc[16];
    load_mu2(qa, pa - 3 * 32);
    load_mu2(qb, pa - 3 * 32 + 512);
    MU2_GROUP(wg_cv_n64, acc1, qa, du, 0);
    load_mu2(qc, pa - 3 * 32 + 1024);
    MU2_GROUP(wg_cv_n64, acc1, qb, du - 16, 1);
    wg_wait<1>();
    load_mu2(qa, pa - 3 * 32 + 1536);
    MU2_GROUP(wg_cv_n64, acc1, qc, du - 32, 1);
    wg_wait<1>();
    load_mu2(qb, pa - 3 * 32 + 2048);
    MU2_GROUP(wg_cv_n56, acc2, qa, du + 32 - 48, 0);
    wg_wait<1>();
    load_mu2(qc, pa - 3 * 32 + 2560);
    MU2_GROUP(wg_cv_n56, acc2, qb, du + 32 - 64, 1);
    wg_wait<1>();
    load_mu2(qa, pa - 3 * 32 + 3072);
    MU2_GROUP(wg_cv_n56, acc2, qc, du + 32 - 80, 1);
    wg_wait<1>();
    load_mu2(qb, pa - 3 * 32 + 3584);
    MU2_GROUP(wg_cv_n40, acc4, qa, du + 96 - 96, 0);
    wg_wait<1>();
    qc[2] = lds32(pa - 96 + 4096); qc[0] = lds32(pa - 64 + 4096); qc[1] = lds32(pa - 32 + 4096); qc[4] = lds32(pa + 4096); qc[5] = lds32(pa + 32 + 4096);
    MU2_GROUP(wg_cv_n40, acc4, qb, du + 96 - 112, 1);
    wg_wait<1>();
    load_far(qa, pa + PAW * 4 - 7 * 32);
    fix_mu(qc, 0);
    wg_fence();
    wg_cv_n40(acc4, qc[0], qc[1], qc[2], qc[3], du + 96 - 128 + 2, 1);
    wg_cv_n40(acc4, qc[4], qc[5], qc[6], qc[7], du + 96 - 128, 1);
    wg_commit();
    wg_wait<1>();
    load_far(qb, pa + (PAW + 128) * 4 - 7 * 32);
    mbar_wait(bar + 8 * B_B97, layer);
    FAR_GROUP(acc3, qa, d9, 0);
    FAR_GROUP(acc3, qb, d9 + (2048 >> 4), 1);
    wg_wait<0>();
    pin_regs(acc1); pin_regs(acc2); pin_regs(acc4); pin_regs(acc3);
    TS(5 + 2 * v + 20 * layer);

#pragma unroll
    for (int i = 0; i < 28; i++) acc1[4 + i] += acc2[i];
#pragma unroll
    for (int i = 0; i < 20; i++) acc1[12 + i] += acc4[i];
    if (wp >= 2) {
      const int src = (lane & ~3) | ((c + 3) & 3);
#pragma unroll
      for (int nb = 7; nb >= 0; nb--)
#pragma unroll
        for (int hh = 0; hh < 2; hh++) {
          const float cur1 = acc1[4 * nb + 2 * hh + 1];
          const float prev1 = nb ? acc1[4 * (nb - 1) + 2 * hh + 1] : 0.f;
          const float sh = __shfl_sync(0xffffffffu, c == 3 ? prev1 : cur1, src);
          acc1[4 * nb + 2 * hh + 1] = acc1[4 * nb + 2 * hh];
          acc1[4 * nb + 2 * hh] = sh;
        }
    }
    {
      const uint32_t ea = ex + (wp >> 1) * 4096 + (wp & 1) * 2048 + lane * 8;
#pragma unroll
      for (int j = 0; j < 8; j++) {
        const float a = wp >= 2 ? acc1[2 * j] : acc1[16 + 2 * j], b = wp >= 2 ? acc1[2 * j + 1] : acc1[16 + 2 * j + 1];
        stsf2(ea + j * 256, a, b);
      }
#pragma unroll
      for (int nb = 0; nb < 2; nb++)
#pragma unroll
        for (int hh = 0; hh < 2; hh++) {
          const int z = 16 * (16 * wp + g + 8 * hh) + 8 * nb + 2 * c;
          stsf2(y3 + (z ^ (((z >> 6) & 3) << 3)) * 4, acc3[4 * nb + 2 * hh], acc3[4 * nb + 2 * hh + 1]);
        }
    }
    bar_sync(1 + w, 128);
    {
      const float kinv = v ? kinvB : kinvA;
      const int hi = wp >> 1, wq = wp & 1;
      float yv[16];
      const uint32_t ea = ex + (hi ^ 1) * 4096 + wq * 2048 + lane * 8;
#pragma unroll
      for (int j = 0; j < 8; j++) {
        const float2 e = ldsf2(ea + j * 256);
        yv[2 * j] = e.x + (hi ? acc1[16 + 2 * j] : acc1[2 * j]);
        yv[2 * j + 1] = e.y + (hi ? acc1[16 + 2 * j + 1] : acc1[2 * j + 1]);
      }
      if (hi) {
#pragma unroll
        for (int j = 0; j < 16; j++) {
          const int z = 32 * (8 * (j >> 2) + 2 * c + (j & 1)) + 16 * wq + g + 8 * ((j >> 1) & 1);
          yv[j] += ldsf(y3 + (z ^ (((z >> 6) & 3) << 3)) * 4);
        }
      }
      const int mat = lane >> 3, ib = 32 * hi + (lane & 7) + 8 * (mat >> 1), r8 = 2 * wq + (mat & 1);
      uint32_t xr[8], ur[8];
#pragma unroll
      for (int h2 = 0; h2 < 2; h2++) {
        const int i = ib + 16 * h2;
        ldsm4t(sb + CV_XS + slot * 4096 + i * 64 + r8 * 16, xr[4 * h2], xr[4 * h2 + 1], xr[4 * h2 + 2], xr[4 * h2 + 3]);
        ldsm4t(u_chunk(ub, 4 * i + r8), ur[4 * h2], ur[4 * h2 + 1], ur[4 * h2 + 2], ur[4 * h2 + 3]);
      }
      uint32_t o[8];
#pragma unroll
      for (int j = 0; j < 8; j++) {
        const uint32_t yy = pack_bf(yv[2 * j] * kinv, yv[2 * j + 1] * kinv);
        const float2 uf = unpack_h(ur[j]);
        o[j] = bf2_add(xr[j], bf2_add(yy, pack_bf(uf.x * dsk, uf.y * dsk)));
      }
      const uint32_t ob = sb + CV_B97 + slot * 4096;
#pragma unroll
      for (int h2 = 0; h2 < 2; h2++) {
        const int i = ib + 16 * h2;
        stsm4t(ob + i * 64 + ((r8 ^ ((i >> 1) & 3)) << 4), o[4 * h2], o[4 * h2 + 1], o[4 * h2 + 2], o[4 * h2 + 3]);
      }
      bar_sync(1 + w, 128);
      const int i = t >> 1, c0 = (t & 1) * 2;
      const uint4 o0 = lds128(ob + i * 64 + ((c0 ^ ((i >> 1) & 3)) << 4)), o1 = lds128(ob + i * 64 + (((c0 + 1) ^ ((i >> 1) & 3)) << 4));
      uint4* dst = reinterpret_cast<uint4*>(xout + ch * SEQ + t * 16);
      dst[0] = o0;
      dst[1] = o1;
      __syncwarp();
      if (lane == 0) mbar_arrive(bar + 8 * (B_PUB + 2 * w + v));
      const uint32_t oo[8] = {o0.x, o0.y, o0.z, o0.w, o1.x, o1.y, o1.z, o1.w};
#pragma unroll
      for (int k = 0; k < 8; k++) {
        const float lo = bf_lo(oo[k]), hi2 = bf_hi(oo[k]);
        ps[2 * k] += lo; pq[2 * k] = fmaf(lo, lo, pq[2 * k]);
        ps[2 * k + 1] += hi2; pq[2 * k + 1] = fmaf(hi2, hi2, pq[2 * k + 1]);
      }
    }
    TS(6 + 2 * v + 20 * layer);
  }
  fence_async_smem();
  __syncwarp();
  if (lane == 0) mbar_arrive(bar + 8 * B_CONVDONE);
  const uint32_t sa = sb + SM_MISC + t * 128;
  if (w == 0) {
#pragma unroll
    for (int i = 0; i < 8; i++)
      sts128(sa + ((i ^ (t & 7)) << 4), make_uint4(__float_as_uint(ps[2 * i]), __float_as_uint(pq[2 * i]), __float_as_uint(ps[2 * i + 1]), __float_as_uint(pq[2 * i + 1])));
    bar_arrive(4, 256);
  } else {
    bar_sync(4, 256);
#pragma unroll
    for (int i = 0; i < 8; i++) {
      const uint32_t a = sa + ((i ^ (t & 7)) << 4);
      const uint4 o4 = lds128(a);
      sts128(a, make_uint4(__float_as_uint(ps[2 * i] + __uint_as_float(o4.x)), __float_as_uint(pq[2 * i] + __uint_as_float(o4.y)),
                           __float_as_uint(ps[2 * i + 1] + __uint_as_float(o4.z)), __float_as_uint(pq[2 * i + 1] + __uint_as_float(o4.w))));
    }
    fence_async_smem();
    __syncwarp();
    if (lane == 0) mbar_arrive(bar + 8 * B_STAGED);
  }
}

struct RowC { float a1[2], b1[2], r[2], rm[2]; };

struct CsV { float2 g[2], u[2]; };
__device__ __forceinline__ void g1_ldcs(CsV& c, uint32_t csa) {
#pragma unroll
  for (int j = 0; j < 2; j++) { c.g[j] = ldsf2(csa + j * 32); c.u[j] = ldsf2(csa + 176 * 4 + j * 32); }
}
template <int NB>
__device__ __forceinline__ void g1_slice(const float (&prv)[64], const CsV& c, const RowC& rc, uint32_t* hp) {
  float e[8], u[8];
#pragma unroll
  for (int i = 0; i < 8; i++) {
    const int j = i >> 2, hh = (i >> 1) & 1;
    e[i] = 1.f + ex2f(fmaf(prv[4 * NB + i], rc.a1[hh], ((i & 1) ? c.g[j].y : c.g[j].x) * rc.b1[hh]));
    u[i] = fmaf(prv[32 + 4 * NB + i], rc.r[hh], ((i & 1) ? c.u[j].y : c.u[j].x) * rc.rm[hh]);
  }
#pragma unroll
  for (int i = 0; i < 4; i++) hp[(NB + (i >> 1)) * 256 + (i & 1) * 32] = pack_bf(u[2 * i] * rcpf(e[2 * i]), u[2 * i + 1] * rcpf(e[2 * i + 1]));
}

struct Ring { uint32_t st, ph; };
template <int NV, bool XW>
__device__ __forceinline__ void g1_mma2(float (&acc)[64], uint32_t bar, uint32_t da, uint32_t dw, int kb, int sc0, bool rel, const Ring& rg, int layer) {
#pragma unroll
  for (int h = 0; h < 2; h++) {
    if (XW) mbar_wait(bar + 8 * B_XFULL + 8 * (kb + h), layer);
    mbar_wait(bar + 8 * B_WFULL + 8 * (rg.st + h), rg.ph);
    const uint32_t a = da + (kb + h) * 1024, b = dw + (rg.st + h) * 1024;
    wg_fence();
#pragma unroll
    for (int k = 0; k < 4; k++) {
      if (NV == 0) wg_g1_n128(acc, a + k * 128, b + k * 128, (h | k) ? 1 : sc0);
      else wg_g1_n112(acc, a + k * 128, b + k * 128, (h | k) ? 1 : sc0);
    }
    wg_commit();
    if (h == 0) {
      wg_wait<1>();
      if (rel) mbar_arrive(bar + 8 * B_WEMPTY + 8 * (rg.st ? rg.st - 1 : 5));
    }
  }
}
__device__ __forceinline__ void g1_release(uint32_t bar, bool l0, Ring& rg) {
  wg_wait<1>();
  if (l0) mbar_arrive(bar + 8 * B_WEMPTY + 8 * rg.st);
  rg.st += 2;
  if (rg.st == 6) { rg.st = 0; rg.ph ^= 1; }
}

struct G1Tail { RowC rc; uint32_t csa; uint32_t* hp; };

__device__ __forceinline__ void gemm1_phase(const Params& p, uint32_t sb, int layer, int w, int wp, int lane, int ti, int tj,
                                            float (&accA)[64], float (&accB)[64], G1Tail& tl) {
  const uint32_t bar = sb + SM_BAR;
  const bool l0 = lane == 0;
#pragma unroll
  for (int i = 0; i < 64; i++) { accA[i] = 0.f; accB[i] = 0.f; }
  pin_regs(accA); pin_regs(accB);
  const uint32_t dx = desc_lo(sb + SM_X + w * 8192, 1024), dw = desc_lo(sb + SM_WR, 8192);
  Ring rg; rg.st = 0; rg.ph = 0;
#pragma unroll 1
  for (int kb = 0; kb < 4; kb += 2) {
    g1_mma2<0, true>(accA, bar, dx, dw, kb, kb, l0 && kb > 0, rg, layer);
    if (kb == 0) TS(9 + 20 * layer);
    g1_release(bar, l0, rg);
  }
#pragma unroll 1
  for (int kb = 0; kb < 4; kb += 2) {
    g1_mma2<0, false>(accB, bar, dx, dw, kb, kb, l0, rg, layer);
    g1_release(bar, l0, rg);
  }
  TS(18 + 20 * layer);
#pragma unroll 1
  for (int kb = 4; kb < 8; kb += 2) {
    g1_mma2<0, true>(accA, bar, dx, dw, kb, 1, l0, rg, layer);
    g1_release(bar, l0, rg);
  }
  TS(10 + 20 * layer);
  RowC& rc = tl.rc;
  uint32_t* hp = reinterpret_cast<uint32_t*>(p.sc->h) + ((2 * ti + w) * 24 + tj) * 2048 + 2 * wp * 32 + lane;
  const uint32_t csa = sb + SM_CS + 2 * (lane & 3) * 4;
  mbar_wait(bar + 8 * B_STFULL, layer);
  if (layer == 0) mbar_wait(bar + 8 * B_CSFULL, 0);
#pragma unroll
  for (int hh = 0; hh < 2; hh++) {
    const float2 mr = ldsf2(sb + SM_ST + (w * 64 + 16 * wp + (lane >> 2) + 8 * hh) * 8);
    rc.a1[hh] = -1.4426950408889634f * mr.y; rc.b1[hh] = 1.4426950408889634f * mr.y * mr.x;
    rc.r[hh] = mr.y; rc.rm[hh] = -mr.y * mr.x;
  }
  if (w == 1) bar_sync(6, 256);
#define G1_IT(ACC, SRC, NV, KB, SC0, NB, CS, HP, FIRST)                        \
  {                                                                            \
    CsV c, c2;                                                                 \
    g1_ldcs(c, (CS) + (NB) * 32);                                              \
    g1_mma2<NV, false>(ACC, bar, dx, dw, KB, SC0, l0, rg, 0);                  \
    if (FIRST) { pin_regs(SRC); if (w == 0) bar_arrive(6, 256); }              \
    g1_ldcs(c2, (CS) + (NB) * 32 + 64);                                        \
    g1_slice<NB>(SRC, c, rc, HP);                                              \
    g1_slice<NB + 2>(SRC, c2, rc, HP);                                         \
    g1_release(bar, l0, rg);                                                   \
  }
  G1_IT(accB, accA, 0, 4, 1, 0, csa, hp, true)
  G1_IT(accB, accA, 0, 6, 1, 4, csa, hp, false)
  __syncwarp();
  if (l0) mbar_arrive(bar + 8 * (B_PUB + 2 * w));
  TS(11 + 20 * layer);
  if (w == 1) bar_sync(6, 256);
  G1_IT(accA, accB, 1, 0, 0, 0, csa + 256, hp + 8 * 2048, true)
  G1_IT(accA, accB, 1, 2, 1, 4, csa + 256, hp + 8 * 2048, false)
#undef G1_IT
  __syncwarp();
  if (l0) mbar_arrive(bar + 8 * (B_PUB + 2 * w + 1));
#pragma unroll 1
  for (int kb = 4; kb < 8; kb += 2) {
    g1_mma2<1, false>(accA, bar, dx, dw, kb, 1, l0, rg, 0);
    g1_release(bar, l0, rg);
  }
  wg_wait<0>();
  pin_regs(accA);
  if (l0) { mbar_arrive(bar + 8 * B_WEMPTY + 8 * 5); mbar_arrive(bar + 8 * B_G1DONE); }
  TS(12 + 20 * layer);
  tl.csa = csa + 512;
  tl.hp = hp + 16 * 2048;
}

__device__ __forceinline__ void gemm2_phase(const Params& p, uint32_t sb, int layer, int w, int wp, int lane, int tt, int tq,
                                            int tj, const float (&prv)[64], const G1Tail& tl) {
  const uint32_t bar = sb + SM_BAR;
  const int t = wp * 32 + lane;
  {
    CsV c0, c1, c2;
    g1_ldcs(c0, tl.csa); g1_ldcs(c1, tl.csa + 64); g1_ldcs(c2, tl.csa + 128);
    g1_slice<0>(prv, c0, tl.rc, tl.hp);
    if (tj < 7) { g1_slice<2>(prv, c1, tl.rc, tl.hp); g1_slice<4>(prv, c2, tl.rc, tl.hp); }
    __syncwarp();
    if (lane == 0) mbar_arrive(bar + 8 * (B_PUB + 2 * w));
    TS(13 + 20 * layer);
  }
  float acc[32];
#pragma unroll
  for (int i = 0; i < 32; i++) acc[i] = 0.f;
  pin_regs(acc);
  uint32_t stage = 0, phase = (layer * 3) & 1;
#pragma unroll 1
  for (int n = 0; n < 12; n++) {
    mbar_wait(bar + 8 * (B_G2FULL + stage), phase);
    if (n == 0) TS(14 + 20 * layer);
    if (n == 8) TS(19 + 20 * layer);
    const uint32_t sa = sb + g2_stage_off(stage);
    const uint32_t da = desc_lo(sa + w * 8192, 1024), db = desc_lo(sa + 32768, 1024);
    if (n < 8) {
      wg_fence();
#pragma unroll
      for (int k = 0; k < 4; k++) wg_g2_n64(acc, da + k * 128, db + k * 128, (n | k) != 0);
#pragma unroll
      for (int k = 0; k < 4; k++) wg_g2_n64(acc, da + 1024 + k * 128, db + 512 + k * 128, 1);
      wg_commit();
    } else if (n < 11) {
      wg_fence();
#pragma unroll
      for (int k = 0; k < 3; k++) wg_g2_n64(acc, da + k * 128, db + k * 128, 1);
#pragma unroll
      for (int k = 0; k < 3; k++) wg_g2_n64(acc, da + 1024 + k * 128, db + 512 + k * 128, 1);
      wg_commit();
    } else {
      wg_fence();
#pragma unroll
      for (int k = 0; k < 3; k++) wg_g2_n64(acc, da + k * 128, db + k * 128, 1);
      wg_g2_n64(acc, da + 1024, db + 512, 1);
      wg_commit();
    }
    wg_wait<1>();
    if (n > 0 && lane == 0) mbar_arrive(bar + 8 * (B_G2EMPTY + ((stage + 3) & 3)));
    if (++stage == 4) { stage = 0; phase ^= 1; }
  }
  wg_wait<0>();
  pin_regs(acc);
  if (lane == 0) mbar_arrive(bar + 8 * (B_G2EMPTY + 3));
  TS(15 + 20 * layer);
  mbar_wait(bar + 8 * B_RESFULL, layer);
  const int g = lane >> 2, c = lane & 3;
  const int mat = lane >> 3;
  const int rrow = 64 * w + 16 * wp + (lane & 7) + 8 * (mat & 1);
  const uint32_t ra = sb + SM_RES + rrow * 128;
  uint32_t o[16];
#pragma unroll
  for (int nb = 0; nb < 8; nb += 2) {
    uint32_t r0, r1, r2, r3;
    ldsm4(ra + (((nb + (mat >> 1)) ^ (rrow & 7)) << 4), r0, r1, r2, r3);
    const uint32_t rr[4] = {r0, r1, r2, r3};
#pragma unroll
    for (int k = 0; k < 4; k++) {
      const int a = 4 * (nb + (k >> 1)) + 2 * (k & 1);
      o[2 * nb + k] = bf2_add(rr[k], pack_bf(acc[a], acc[a + 1]));
    }
  }
  if (layer == 0) {
#pragma unroll
    for (int nb = 0; nb < 8; nb += 2)
      stsm4(ra + (((nb + (mat >> 1)) ^ (rrow & 7)) << 4), o[2 * nb], o[2 * nb + 1], o[2 * nb + 2], o[2 * nb + 3]);
    __syncwarp();
#pragma unroll
    for (int i = 0; i < 4; i++) {
      const int idx = lane + 32 * i, row = 64 * w + 16 * wp + (idx >> 3), ch = idx & 7;
      const uint4 v = lds128(sb + SM_RES + row * 128 + ((ch ^ (row & 7)) << 4));
      *reinterpret_cast<uint4*>(p.sc->xT[1] + (128 * tq + row) * SEQ + 64 * tt + 8 * ch) = v;
    }
    float v[32];
#pragma unroll
    for (int nb = 0; nb < 8; nb++) {
      const uint32_t a = o[2 * (nb & ~1) + 2 * (nb & 1)], b = o[2 * (nb & ~1) + 2 * (nb & 1) + 1];
      const float a0 = bf_lo(a), a1 = bf_hi(a), b0 = bf_lo(b), b1 = bf_hi(b);
      v[4 * nb] = a0 + b0; v[4 * nb + 1] = a1 + b1;
      v[4 * nb + 2] = fmaf(a0, a0, b0 * b0); v[4 * nb + 3] = fmaf(a1, a1, b1 * b1);
    }
    const bool s4 = lane & 16, s3 = lane & 8, s2 = lane & 4;
#pragma unroll
    for (int i = 0; i < 16; i++) {
      const float snd = s4 ? v[i] : v[16 + i], kp = s4 ? v[16 + i] : v[i];
      v[i] = kp + __shfl_xor_sync(0xffffffffu, snd, 16);
    }
#pragma unroll
    for (int i = 0; i < 8; i++) {
      const float snd = s3 ? v[i] : v[8 + i], kp = s3 ? v[8 + i] : v[i];
      v[i] = kp + __shfl_xor_sync(0xffffffffu, snd, 8);
    }
#pragma unroll
    for (int i = 0; i < 4; i++) {
      const float snd = s2 ? v[i] : v[4 + i], kp = s2 ? v[4 + i] : v[i];
      v[i] = kp + __shfl_xor_sync(0xffffffffu, snd, 4);
    }
    {
      const int nbf = (s4 ? 4 : 0) + (s3 ? 2 : 0) + (s2 ? 1 : 0), col = 8 * nbf + 2 * c;
      const uint32_t scr = sb + SM_G2S + (w * 4 + wp) * 512 + col * 8;
      stsf2(scr, v[0], v[2]);
      stsf2(scr + 8, v[1], v[3]);
    }
    bar_sync(4, 256);
    if (w == 0) {
      float s = 0.f;
#pragma unroll
      for (int k = 0; k < 8; k++) s += ldsf(sb + SM_G2S + k * 512 + t * 4);
      atomicAdd(reinterpret_cast<float*>(p.sc->stat3) + 128 * tt + t, s);
    }
    __syncwarp();
    if (lane == 0) mbar_arrive(bar + 8 * (B_PUB + 2 * w + 1));
    fence_async_smem();
    __syncwarp();
    if (lane == 0) mbar_arrive(bar + 8 * B_G2DONE);
  } else {
    const uint32_t oa = sb + SM_G2S + w * 8192;
#pragma unroll
    for (int nb = 0; nb < 8; nb += 2) {
      const int l = 8 * (nb + (mat >> 1)) + (lane & 7), chunk = 2 * wp + (mat & 1);
      stsm4t(oa + l * 128 + ((chunk ^ (l & 7)) << 4), o[2 * nb], o[2 * nb + 1], o[2 * nb + 2], o[2 * nb + 3]);
    }
    bar_sync(1 + w, 128);
#pragma unroll
    for (int i = 0; i < 4; i++) {
      const int idx = t + 128 * i, l = idx >> 3, ch = idx & 7;
      const uint4 v = lds128(oa + l * 128 + ((ch ^ (l & 7)) << 4));
      *reinterpret_cast<uint4*>(p.out + (64 * tt + l) * DM + 128 * tq + 64 * w + 8 * ch) = v;
    }
  }
  TS(16 + 20 * layer);
  (void)g;
}

__global__ void __launch_bounds__(NTHR, 1)
fused_s4d_glu_kernel(const __grid_constant__ CUtensorMap tmG, const __grid_constant__ CUtensorMap tmU, const __grid_constant__ CUtensorMap tmWd,
                     const __grid_constant__ CUtensorMap tmX1, const __grid_constant__ CUtensorMap tmX3,
                     const __grid_constant__ CUtensorMap tmR1, const __grid_constant__ CUtensorMap tmR3,
                     const __grid_constant__ CUtensorMap tmX0, const __grid_constant__ CUtensorMap tmCG,
                     const __grid_constant__ CUtensorMap tmCU, const Params p) {
  extern __shared__ __align__(1024) unsigned char smem[];
  const uint32_t sb = smem_u32(smem);
  const uint32_t bar = sb + SM_BAR;
  const int tid = threadIdx.x, lane = tid & 31;
  const int warp = __shfl_sync(0xffffffffu, tid >> 5, 0);
  const int cta = blockIdx.x;
  const int grp = cta >> 4, r16 = cta & 15;
  const int ti = 4 * (grp & 3) + (r16 & 3), tj = 4 * (grp >> 2) + (r16 >> 2);
  const int tt = 4 * grp + (r16 >> 2), tq = r16 & 3;
  TS(2);
  uint32_t kraw[10];
  if (warp < 8) {
#pragma unroll
    for (int v = 0; v < 2; v++) {
      const int ch = 4 * cta + 2 * v + (warp >> 2), idx = ch * NMODE + (tid & 127);
      asm volatile("ld.global.nc.u16 %0, [%1];" : "=r"(kraw[5 * v]) : "l"(p.logA + idx));
      asm volatile("ld.global.nc.u16 %0, [%1];" : "=r"(kraw[5 * v + 1]) : "l"(p.Aim + idx));
      asm volatile("ld.global.nc.u16 %0, [%1];" : "=r"(kraw[5 * v + 2]) : "l"(p.Cre + idx));
      asm volatile("ld.global.nc.u16 %0, [%1];" : "=r"(kraw[5 * v + 3]) : "l"(p.Cim + idx));
      asm volatile("ld.global.nc.u16 %0, [%1];" : "=r"(kraw[5 * v + 4]) : "l"(p.logdt + ch));
    }
  }
  uint4 xrow[8];
  if (warp >= 8) {
#pragma unroll
    for (int r = 0; r < 4; r++) {
      const bf16* src = p.x0 + (16 * cta + 4 * (warp - 8) + r) * DM + lane * 8;
      xrow[2 * r] = ldg128_nc(src); xrow[2 * r + 1] = ldg128_nc(src + 256);
    }
  }
  if (warp >= 8 && lane == 0) {
    if (sb & 1023) __trap();
    const uint32_t codes = warp == 8 ? (uint32_t)LO_CODES : (warp == 9 ? (uint32_t)(LO_CODES >> 32) : (warp == 10 ? (uint32_t)HI_CODES : (uint32_t)(HI_CODES >> 32)));
    const uint32_t b0 = bar + (warp - 8) * 128;
#pragma unroll
    for (int i = 0; i < 16; i++) mbar_init(b0 + 8 * i, 1u << ((codes >> (2 * i)) & 3));
    asm volatile("fence.mbarrier_init.release.cluster;" ::: "memory");
  }
  __syncthreads();

  if (warp < 8) {
    asm volatile("setmaxnreg.inc.sync.aligned.u32 224;");
    TS(0);
    const int w = warp >> 2, wp = warp & 3;
    const int t = wp * 32 + lane;
    KParam kp[2];
#pragma unroll
    for (int v = 0; v < 2; v++) {
      uint32_t f[5];
#pragma unroll
      for (int k = 0; k < 5; k++) asm volatile("shl.b32 %0, %1, 16;" : "=r"(f[k]) : "r"(kraw[5 * v + k]));
      kp[v].logA = __uint_as_float(f[0]); kp[v].aim = __uint_as_float(f[1]); kp[v].cre = __uint_as_float(f[2]);
      kp[v].cim = __uint_as_float(f[3]); kp[v].logdt = __uint_as_float(f[4]);
    }
    float kinv[2];
    kgen(sb, w, wp, lane, kp, kinv);
    strip_transpose(sb, warp, lane, cta);
    TS(1);
#pragma unroll 1
    for (int layer = 0; layer < 2; layer++) {
      conv_phase(p, sb, layer, w, wp, lane, cta, kinv[0], kinv[1]);
      float accA[64], accB[64];
      G1Tail tl;
      gemm1_phase(p, sb, layer, w, wp, lane, ti, tj, accA, accB, tl);
      gemm2_phase(p, sb, layer, w, wp, lane, tt, tq, tj, accA, tl);
    }
    __syncwarp();
    if (lane == 0) mbar_arrive(bar + 8 * B_KDONE);
  } else {
    asm volatile("setmaxnreg.dec.sync.aligned.u32 56;");
    const int wv = warp - 8;
    unsigned ep1;
    asm volatile("ld.relaxed.gpu.global.u32 %0, [%1];" : "=r"(ep1) : "l"(&p.sc->epoch) : "memory");
    ep1 += 1;
    {
      uint4 (&v)[8] = xrow;
      if (wv == 0 && elect_one()) {
        const uint32_t fb = bar + 8 * B_STRIP;
        mbar_expect(fb, 32768);
#pragma unroll 1
        for (int k = 0; k < 8; k++) tma_2d(sb + SM_STRIP + k * 4096, &tmX0, 8 * (cta >> 1), 256 * k, fb);
      }
      __syncwarp();
      if (lane < 9) {
        float2* z = (lane == 0 ? p.sc->stat3 : p.sc->stat2[(lane - 1) >> 2][(lane - 1) & 3]) + 16 * cta + 4 * wv;
        *reinterpret_cast<uint4*>(z) = make_uint4(0, 0, 0, 0);
        *reinterpret_cast<uint4*>(z + 2) = make_uint4(0, 0, 0, 0);
      }
      float a[8];
#pragma unroll
      for (int r = 0; r < 4; r++) {
        const uint32_t xx[8] = {v[2 * r].x, v[2 * r].y, v[2 * r].z, v[2 * r].w, v[2 * r + 1].x, v[2 * r + 1].y, v[2 * r + 1].z, v[2 * r + 1].w};
        float s0 = 0.f, s1 = 0.f, q0 = 0.f, q1 = 0.f;
#pragma unroll
        for (int k = 0; k < 8; k++) { const float lo = bf_lo(xx[k]), hi = bf_hi(xx[k]); s0 += lo; s1 += hi; q0 = fmaf(lo, lo, q0); q1 = fmaf(hi, hi, q1); }
        a[2 * r] = s0 + s1; a[2 * r + 1] = q0 + q1;
      }
      const bool s4 = lane & 16, s3 = lane & 8, s2 = lane & 4;
#pragma unroll
      for (int i = 0; i < 4; i++) { const float snd = s4 ? a[i] : a[4 + i], kp2 = s4 ? a[4 + i] : a[i]; a[i] = kp2 + __shfl_xor_sync(0xffffffffu, snd, 16); }
#pragma unroll
      for (int i = 0; i < 2; i++) { const float snd = s3 ? a[i] : a[2 + i], kp2 = s3 ? a[2 + i] : a[i]; a[i] = kp2 + __shfl_xor_sync(0xffffffffu, snd, 8); }
      { const float snd = s2 ? a[0] : a[1], kp2 = s2 ? a[1] : a[0]; a[0] = kp2 + __shfl_xor_sync(0xffffffffu, snd, 4); }
      a[0] += __shfl_xor_sync(0xffffffffu, a[0], 2);
      a[0] += __shfl_xor_sync(0xffffffffu, a[0], 1);
      if ((lane & 3) == 0) reinterpret_cast<float*>(p.sc->stat1)[2 * (16 * cta + 4 * wv) + (lane >> 2)] = a[0];
      bar_sync(3, 128);
      if (wv == 0 && lane == 0) TSA(21);
    }
    if (wv == 3) {
      if (elect_one()) {
        mbar_wait(bar + 8 * B_PTDONE, 0);
        asm volatile("cp.async.bulk.global.shared::cta.bulk_group [%0], [%1], %2;" ::"l"(p.sc->ptab + 4 * cta * PTW), "r"(sb + SM_PT), "n"(4 * PTW * 4) : "memory");
        asm volatile("cp.async.bulk.commit_group;" ::: "memory");
        asm volatile("cp.async.bulk.wait_group 0;" ::: "memory");
        fence_async_all();
        mbar_arrive(bar + 8 * B_PTSAVED);
      }
      __syncwarp();
      if (elect_one()) {
        mbar_wait(bar + 8 * B_CSDONE, 0);
        flag_wait(&p.sc->flag[F_CS * 8], ep1 * 172);
        fence_async_all();
        const uint32_t fb = bar + 8 * B_CSFULL;
        mbar_expect(fb, 1408);
        bulk_g2s(sb + SM_CS, p.sc->cs + 176 * tj, 704, fb);
        bulk_g2s(sb + SM_CS + 704, p.sc->cs + CSP + 176 * tj, 704, fb);
      }
      __syncwarp();
#pragma unroll 1
      for (int layer = 0; layer < 2; layer++) {
        if (elect_one()) {
          mbar_wait(bar + 8 * B_STAGED, layer);
          asm volatile("cp.reduce.async.bulk.global.shared::cta.bulk_group.add.f32 [%0], [%1], 16384;" ::"l"(p.sc->stat2[layer][cta & 3]), "r"(sb + SM_MISC) : "memory");
          asm volatile("cp.async.bulk.commit_group;" ::: "memory");
          asm volatile("cp.async.bulk.wait_group.read 0;" ::: "memory");
          mbar_arrive(bar + 8 * B_TAILDONE);
          asm volatile("cp.async.bulk.wait_group 0;" ::: "memory");
          fence_async_all();
          flag_publish(&p.sc->flag[(F_S + layer) * 8]);
          flag_wait(&p.sc->flag[(F_S + layer) * 8], ep1 * 128);
        }
        __syncwarp();
#pragma unroll 1
        for (int k0 = 0; k0 < 4; k0 += 2) {
          float2 v[8];
#pragma unroll
          for (int k = 0; k < 2; k++) {
            const int l = 128 * ti + 32 * (k0 + k) + lane, tq16 = l >> 4;
            const float* src = reinterpret_cast<const float*>(p.sc->stat2[layer]) + tq16 * 32 + ((((l & 15) >> 1) ^ (tq16 & 7)) << 2) + (l & 1) * 2;
#pragma unroll
            for (int r = 0; r < 4; r++) asm volatile("ld.global.cg.v2.f32 {%0, %1}, [%2];" : "=f"(v[4 * k + r].x), "=f"(v[4 * k + r].y) : "l"(src + r * 2 * SEQ) : "memory");
          }
#pragma unroll
          for (int k = 0; k < 2; k++) {
            const float2 mr = ln_finalize((v[4 * k].x + v[4 * k + 1].x) + (v[4 * k + 2].x + v[4 * k + 3].x), (v[4 * k].y + v[4 * k + 1].y) + (v[4 * k + 2].y + v[4 * k + 3].y));
            stsf2(sb + SM_ST + (32 * (k0 + k) + lane) * 8, mr.x, mr.y);
          }
        }
        __syncwarp();
        if (lane == 0) mbar_arrive(bar + 8 * B_STFULL);
      }
      if (lane == 0) mbar_wait_checked(bar + 8 * B_KDONE, 0);
    } else if (wv == 1 || wv == 2) {
      const int unit = cta + 128 * (wv - 1);
      if (unit < 172) {
        const int mat = unit / 86, col0 = (unit - mat * 86) * 16;
        const uint32_t buf = sb + SM_X + (wv - 1) * 16384, lb = bar + 8 * (B_CSL + wv - 1);
        if (elect_one()) {
          mbar_wait(bar + 8 * B_KGDONE, 0);
          mbar_expect(lb, 16384);
          tma_2d(buf, mat ? &tmCU : &tmCG, col0, 0, lb);
          tma_2d(buf + 8192, mat ? &tmCU : &tmCG, col0, 256, lb);
        }
        __syncwarp();
        mbar_wait(lb, 0);
        float a[8];
#pragma unroll
        for (int k = 0; k < 8; k++) a[k] = 0.f;
#pragma unroll 4
        for (int i = 0; i < 32; i++) {
          const uint4 v = lds128(buf + i * 512 + lane * 16);
          a[0] += bf_lo(v.x); a[1] += bf_hi(v.x); a[2] += bf_lo(v.y); a[3] += bf_hi(v.y);
          a[4] += bf_lo(v.z); a[5] += bf_hi(v.z); a[6] += bf_lo(v.w); a[7] += bf_hi(v.w);
        }
#pragma unroll
        for (int k = 0; k < 8; k++)
#pragma unroll
          for (int o = 2; o < 32; o <<= 1) a[k] += __shfl_xor_sync(0xffffffffu, a[k], o);
        if (lane < 2) {
          float4* dst = reinterpret_cast<float4*>(p.sc->cs + mat * CSP + col0 + lane * 8);
          dst[0] = make_float4(a[0], a[1], a[2], a[3]);
          dst[1] = make_float4(a[4], a[5], a[6], a[7]);
        }
        __syncwarp();
        if (elect_one()) { flag_publish(&p.sc->flag[F_CS * 8]); if (wv == 1) TSA(41); }
        __syncwarp();
      }
      if (lane == 0) mbar_arrive(bar + 8 * B_CSDONE);
      __syncwarp();
      if (elect_one()) {
          const int w = wv - 1;
#pragma unroll 1
        for (int layer = 0; layer < 2; layer++) {
#pragma unroll 1
          for (int e = 0; e < (layer == 0 ? 6 : 5); e++) {
            mbar_wait(bar + 8 * (B_PUB + 2 * w + (e & 1)), (3 * layer + (e >> 1)) & 1);
            const int f = e < 2 ? F_1 + layer * 2 + e : (e < 5 ? F_2 + layer * 96 + (2 * ti + w) * 3 + (e - 2) : F_3);
            if (layer == 1 && e == 4 && w == 0) TSA(56);
            flag_publish(&p.sc->flag[f * 8]);
            if (layer == 1 && e == 4 && w == 0) TSA(49);
            if (e == 4) mbar_arrive(bar + 8 * B_PUBDONE);
            if (e == 5) mbar_arrive(bar + 8 * B_PUB3);
          }
        }
      }
    } else if (elect_one()) {
      flag_publish(&p.sc->flag[F_0 * 8]);
      TSA(22);
      tmap_prefetch(&tmG); tmap_prefetch(&tmU); tmap_prefetch(&tmX1); tmap_prefetch(&tmWd);
      tmap_prefetch(&tmR1); tmap_prefetch(&tmX3); tmap_prefetch(&tmR3);
      l2_prefetch(reinterpret_cast<const char*>(p.wd) + cta * 11008, 11008);
      uint32_t wst = 0, wph = 1;
      auto issue_w = [&](int n) {
        TRA(n * 4);
        mbar_wait(bar + 8 * (B_WEMPTY + wst), wph);
        const uint32_t fb = bar + 8 * (B_WFULL + wst), dst = sb + SM_WR + wst * 16384;
        const int pp = n < 16 ? (n >> 2) & 1 : 2, kb = n < 16 ? (n & 3) + ((n >> 1) & 4) : n - 16;
        const int f0 = 176 * tj + 64 * pp;
        mbar_expect(fb, 16384);
        tma_4d(dst, &tmG, f0, 0, kb >> 2, 32 * (kb & 3), fb);
        tma_4d(dst + 8192, &tmU, f0, 0, kb >> 2, 32 * (kb & 3), fb);
        if (++wst == 6) { wst = 0; wph ^= 1; }
      };
#pragma unroll 1
      for (int layer = 0; layer < 2; layer++) {
        const CUtensorMap* tmX = layer ? &tmX3 : &tmX1;
        {
          flag_wait(&p.sc->flag[(layer ? F_3 : F_0) * 8], ep1 * (layer ? 256 : 128));
          TSA(layer ? 48 : 40);
          fence_async_all();
          const uint32_t fb = bar + 8 * B_XSFULL;
          if (layer == 0) {
            if (cta == 0) asm volatile("st.relaxed.gpu.global.u32 [%0], %1;" ::"l"(&p.sc->epoch), "r"(ep1) : "memory");
            mbar_wait(bar + 8 * B_KGDONE, 0);
            mbar_expect(fb, 16384);
          } else {
            mbar_expect(fb, 32768);
            bulk_g2s(sb + CV_XS, p.sc->xT[1] + 4 * cta * SEQ, 16384, fb);
          }
          bulk_g2s(sb + CV_B97, layer ? p.sc->stat3 : p.sc->stat1, 16384, fb);
          if (layer == 0) {
                  issue_w(0);
            mbar_wait(bar + 8 * B_STRIPDONE, 0);
          } else {
            mbar_wait(fb, 1);
            const uint32_t pb = bar + 8 * B_PTFULL;
            mbar_expect(pb, 4 * PTW * 4);
            bulk_g2s(sb + SM_PT, p.sc->ptab + 4 * cta * PTW, 4 * PTW * 4, pb);
            issue_w(0);
          }
          issue_w(1);
          issue_w(2);
        }
        if (layer == 0) mbar_wait(bar + 8 * B_CSDONE, 0);
#pragma unroll 1
        for (int b = 0; b < 2; b++) {
          if (b == 1) {
            TSA(42 + 8 * layer);
            mbar_wait(bar + 8 * B_CONVDONE, layer);
            if (layer == 0) mbar_wait(bar + 8 * B_PTSAVED, 0);
            issue_w(3);
            issue_w(4);
            mbar_wait(bar + 8 * B_TAILDONE, layer);
            issue_w(5);
            issue_w(6);
            issue_w(7);
          }
          flag_wait(&p.sc->flag[(F_1 + layer * 2 + b) * 8], ep1 * 256);
          if (layer == 1 && b == 1) TSA(59);
          fence_async_all();
#pragma unroll 1
          for (int k = 0; k < 4; k++) {
            const uint32_t fb = bar + 8 * (B_XFULL + 4 * b + k);
            mbar_expect(fb, 16384);
            tma_5d(sb + SM_X + (4 * b + k) * 16384, tmX, 0, 0, b, 32 * k, 2 * ti, fb);
          }
        }
        TSA(43 + 8 * layer);
#pragma unroll 1
        for (int n = 8; n < 24; n++) issue_w(n);
        uint32_t st2 = 0, ph2 = ((layer * 3) & 1) ^ 1;
        const bf16* hsrc = p.sc->h + tt * 24 * 4096;
        const unsigned* f2 = &p.sc->flag[(F_2 + layer * 96 + tt * 3) * 8];
        flag_wait(f2, ep1 * 8);
        fence_async_all();
        TSA(45 + 8 * layer);
        mbar_wait(bar + 8 * (B_WEMPTY + 0), 1);
        mbar_wait(bar + 8 * (B_WEMPTY + 1), 1);
        mbar_wait(bar + 8 * (B_WEMPTY + 2), 1);
#pragma unroll 1
        for (int n = 0; n < 12; n++) {
          const int pp = n >> 2, j = 2 * (n & 3);
          const uint32_t fb = bar + 8 * (B_G2FULL + st2), dst = sb + g2_stage_off(st2);
          const uint32_t hbytes = pp < 2 ? 16384 : (j < 6 ? 14336 : 10240);
          if (n == 1) { mbar_wait(bar + 8 * B_G1DONE, layer); TSA(44 + 8 * layer); }
          if (n == G2_HOLD) mbar_wait(bar + 8 * B_PUBDONE, layer);
          if (j == 0 && pp > 0) { flag_wait(f2 + pp * 8, ep1 * 8); fence_async_all(); TSA(45 + pp + 8 * layer); }
          mbar_wait(bar + 8 * (B_G2EMPTY + st2), ph2);
          mbar_expect(fb, 32768 + hbytes);
          tma_3d(dst, &tmWd, 0, 176 * j + 64 * pp, 2 * tq, fb);
          tma_3d(dst + 16384, &tmWd, 0, 176 * j + 176 + 64 * pp, 2 * tq, fb);
          bulk_g2s(dst + 32768, hsrc + n * 8192, hbytes, fb);
          if (n == 3) {
            const uint32_t rb = bar + 8 * B_RESFULL;
            mbar_expect(rb, 16384);
            tma_2d(sb + SM_RES, layer ? &tmR3 : &tmR1, 64 * tt, 128 * tq, rb);
          }
          if (++st2 == 4) { st2 = 0; ph2 ^= 1; }
        }
        if (layer == 0) { mbar_wait(bar + 8 * B_G2DONE, 0); mbar_wait(bar + 8 * B_PUB3, 0); }
      }
    }
  }
}

typedef CUresult (*EncodeFn)(CUtensorMap*, CUtensorMapDataType, cuuint32_t, void*, const cuuint64_t*, const cuuint64_t*, const cuuint32_t*,
                             const cuuint32_t*, CUtensorMapInterleave, CUtensorMapSwizzle, CUtensorMapL2promotion, CUtensorMapFloatOOBfill);

void make_map(EncodeFn fn, CUtensorMap* m, const void* base, int rank, const cuuint64_t* dims, const cuuint64_t* strides, const cuuint32_t* box) {
  cuuint32_t es[5] = {1, 1, 1, 1, 1};
  fn(m, CU_TENSOR_MAP_DATA_TYPE_BFLOAT16, rank, const_cast<void*>(base), dims, strides, box, es, CU_TENSOR_MAP_INTERLEAVE_NONE,
     CU_TENSOR_MAP_SWIZZLE_128B, CU_TENSOR_MAP_L2_PROMOTION_L2_128B, CU_TENSOR_MAP_FLOAT_OOB_FILL_NONE);
}

}

extern "C" void kernel_launch(void* const* d_in, const int* in_sizes, int n_in, void* d_out, int out_size) {
  (void)in_sizes; (void)n_in; (void)out_size;
  static EncodeFn enc = nullptr;
  static Scratch* sc = nullptr;
  if (!enc) {
    void* fn = nullptr;
    cudaDriverEntryPointQueryResult qr;
    cudaGetDriverEntryPoint("cuTensorMapEncodeTiled", &fn, cudaEnableDefault, &qr);
    enc = (EncodeFn)fn;
    void* a = nullptr;
    cudaGetSymbolAddress(&a, g_scratch);
    sc = (Scratch*)a;
    cudaFuncSetAttribute(fused_s4d_glu_kernel, cudaFuncAttributeMaxDynamicSharedMemorySize, SM_TOTAL);
  }
  Params p;
  p.x0 = (const bf16*)d_in[0]; p.logA = (const bf16*)d_in[1]; p.Aim = (const bf16*)d_in[2]; p.Cre = (const bf16*)d_in[3];
  p.Cim = (const bf16*)d_in[4]; p.logdt = (const bf16*)d_in[5]; p.Dsk = (const bf16*)d_in[6];
  p.wg = (const bf16*)d_in[8]; p.wu = (const bf16*)d_in[9]; p.wd = (const bf16*)d_in[10];
  p.out = (bf16*)d_out;
  p.sc = sc;
  bf16* xT = &sc->xT[0][0];

  CUtensorMap tmG, tmU, tmWd, tmX1, tmX3, tmR1, tmR3, tmX0, tmCG, tmCU;
  {
    const cuuint64_t dims[4] = {FF, 2, 2, 128}, str[3] = {FF * 2, FF * 4, FF * 8};
    const cuuint32_t box[4] = {64, 2, 1, 32};
    make_map(enc, &tmG, p.wg, 4, dims, str, box);
    make_map(enc, &tmU, p.wu, 4, dims, str, box);
  }
  {
    const cuuint64_t dims[3] = {64, FF, 8}, str[2] = {DM * 2, 128};
    const cuuint32_t box[3] = {64, 64, 2};
    make_map(enc, &tmWd, p.wd, 3, dims, str, box);
  }
  {
    const cuuint64_t dims[5] = {64, 2, 2, 128, 32}, str[4] = {SEQ * 2, SEQ * 4, SEQ * 8, 128};
    const cuuint32_t box[5] = {64, 2, 1, 32, 2};
    make_map(enc, &tmX1, xT, 5, dims, str, box);
    make_map(enc, &tmX3, xT + 2 * DM * SEQ, 5, dims, str, box);
  }
  {
    const cuuint64_t dims[2] = {SEQ, DM}, str[1] = {SEQ * 2};
    const cuuint32_t box[2] = {64, 128};
    make_map(enc, &tmR1, xT, 2, dims, str, box);
    make_map(enc, &tmR3, xT + 2 * DM * SEQ, 2, dims, str, box);
  }
  {
    const cuuint64_t dims[2] = {DM, SEQ}, str[1] = {DM * 2};
    const cuuint32_t box[2] = {8, 256}, es[2] = {1, 1};
    enc(&tmX0, CU_TENSOR_MAP_DATA_TYPE_BFLOAT16, 2, const_cast<bf16*>(p.x0), dims, str, box, es, CU_TENSOR_MAP_INTERLEAVE_NONE,
        CU_TENSOR_MAP_SWIZZLE_NONE, CU_TENSOR_MAP_L2_PROMOTION_L2_128B, CU_TENSOR_MAP_FLOAT_OOB_FILL_NONE);
  }
  {
    const cuuint64_t dims[2] = {FF, DM}, str[1] = {FF * 2};
    const cuuint32_t box[2] = {16, 256}, es[2] = {1, 1};
    enc(&tmCG, CU_TENSOR_MAP_DATA_TYPE_BFLOAT16, 2, const_cast<bf16*>(p.wg), dims, str, box, es, CU_TENSOR_MAP_INTERLEAVE_NONE,
        CU_TENSOR_MAP_SWIZZLE_NONE, CU_TENSOR_MAP_L2_PROMOTION_L2_128B, CU_TENSOR_MAP_FLOAT_OOB_FILL_NONE);
    enc(&tmCU, CU_TENSOR_MAP_DATA_TYPE_BFLOAT16, 2, const_cast<bf16*>(p.wu), dims, str, box, es, CU_TENSOR_MAP_INTERLEAVE_NONE,
        CU_TENSOR_MAP_SWIZZLE_NONE, CU_TENSOR_MAP_L2_PROMOTION_L2_128B, CU_TENSOR_MAP_FLOAT_OOB_FILL_NONE);
  }
  fused_s4d_glu_kernel<<<NCTA, NTHR, SM_TOTAL, cudaStreamPerThread>>>(tmG, tmU, tmWd, tmX1, tmX3, tmR1, tmR3, tmX0, tmCG, tmCU, p);
}
```

```cpp
#include <cuda_runtime.h>
#include <cuda_bf16.h>
#include <cuda_fp16.h>
#include <cuda.h>
#include <stdint.h>

namespace {

typedef __nv_bfloat16 bf16;

constexpr int SEQ = 2048;
constexpr int DM = 512;
constexpr int NMODE = 128;
constexpr int FF = 1376;
constexpr int NCTA = 128;
constexpr int NTHR = 384;
constexpr int CSP = 1408;
constexpr int PAW = 1152;
constexpr int PTW = 1408;
constexpr int SPIN_LIMIT = 1 << 20;

constexpr uint32_t SM_X = 0;
constexpr uint32_t SM_WR = 131072;
constexpr uint32_t SM_MISC = 212992;
constexpr uint32_t SM_SMALL = 229376;
constexpr uint32_t SM_TOTAL = 232448;
constexpr uint32_t SM_CONV = 65536;
constexpr uint32_t CV_U = SM_CONV;
constexpr uint32_t CV_B97 = SM_CONV + 20480;
constexpr uint32_t CV_E0 = SM_CONV + 36864;
constexpr uint32_t CV_XS = SM_CONV + 49152;
constexpr uint32_t CV_E1 = SM_MISC;
constexpr uint32_t KG_A = 0;
constexpr uint32_t KG_B = 32768;
constexpr uint32_t SM_PT = SM_WR + 3 * 16384;
constexpr uint32_t SM_STAT = SM_MISC;
constexpr uint32_t SM_RES = 98304;
constexpr uint32_t SM_G2S = 114688;
constexpr uint32_t G2_STAGE = 49152;
constexpr uint32_t SM_BAR = SM_SMALL;
constexpr uint32_t SM_CS = SM_SMALL + 512;
constexpr uint32_t SM_ST = SM_SMALL + 1920;

enum {
  B_WFULL = 0, B_WEMPTY = 6,
  B_XFULL = 12,
  B_CSFULL = 20,
  B_G2FULL = 21, B_G2EMPTY = 27,
  B_RESFULL = 33,
  B_PTFULL = 34, B_XSFULL = 35,
  B_CONVDONE = 36, B_G1DONE = 37, B_G2DONE = 38,
  B_TAILDONE = 39,
  B_STFULL = 40,
  B_KDONE = 41,
  B_KGDONE = 43,
  B_STAGED = 44,
  B_PTDONE = 47, B_PTSAVED = 48,
  B_RT = 49, B_RTDONE = 51,
  B_PUB = 53,
  B_CSL = 57, B_CSDONE = 59,
  B_PUB3 = 60,
  B_B97 = 61
};
constexpr int bar_log2_count(int i) {
  return (i >= B_WEMPTY && i < B_WEMPTY + 6) || (i >= B_G2EMPTY && i < B_G2EMPTY + 6) || i == B_CONVDONE || i == B_G1DONE || i == B_G2DONE ||
                 i == B_KGDONE || i == B_KDONE || i == B_PTDONE
             ? 3
             : ((i >= B_PUB && i < B_PUB + 4) || i == B_STAGED || i == B_B97 ? 2 : (i == B_CSDONE || i == B_PUB3 ? 1 : 0));
}
constexpr unsigned long long bar_codes(int base) {
  unsigned long long r = 0;
  for (int i = 0; i < 32; i++) r |= (unsigned long long)bar_log2_count(base + i) << (2 * i);
  return r;
}
constexpr unsigned long long LO_CODES = bar_codes(0), HI_CODES = bar_codes(32);
enum { F_0 = 0, F_CS = 1, F_3 = 2, F_W = 3, F_S = 4, F_1 = 8, F_2 = 32, F_COUNT = 224 };

struct Scratch {
  bf16 xT[3][DM * SEQ];
  bf16 h[32 * 24 * 4096];
  bf16 wt[192 * 8192];
  bf16 wdt[96 * 8192];
  uint32_t ptab[DM * PTW];
  float2 stat1[SEQ];
  float2 stat3[SEQ];
  float2 stat2[2][4][SEQ];
  float cs[2 * CSP];
  unsigned flag[F_COUNT * 8];
  unsigned epoch;
};
__device__ __align__(1024) Scratch g_scratch;

struct Params {
  const bf16 *x0, *logA, *Aim, *Cre, *Cim, *logdt, *Dsk, *wg, *wu, *wd;
  bf16* out;
  Scratch* sc;
};

__device__ __forceinline__ uint32_t smem_u32(const void* p) { return (uint32_t)__cvta_generic_to_shared(p); }
__device__ __forceinline__ void mbar_init(uint32_t a, uint32_t c) { asm volatile("mbarrier.init.shared::cta.b64 [%0], %1;" ::"r"(a), "r"(c) : "memory"); }
__device__ __forceinline__ void mbar_expect(uint32_t a, uint32_t b) { asm volatile("mbarrier.arrive.expect_tx.shared::cta.b64 _, [%0], %1;" ::"r"(a), "r"(b) : "memory"); }
__device__ __forceinline__ void mbar_arrive(uint32_t a) { asm volatile("mbarrier.arrive.shared::cta.b64 _, [%0];" ::"r"(a) : "memory"); }
__device__ __forceinline__ void mbar_wait(uint32_t a, uint32_t par) {
  asm volatile("{\n.reg .pred p;\nLW:\nmbarrier.try_wait.parity.shared::cta.b64 p, [%0], %1;\n@!p bra LW;\n}\n" ::"r"(a), "r"(par) : "memory");
}
__device__ __forceinline__ void mbar_wait_checked(uint32_t a, uint32_t par) {
  asm volatile("{\n.reg .pred p;\n.reg .u32 n;\nmov.u32 n, 0;\n"
               "LW:\nmbarrier.try_wait.parity.shared::cta.b64 p, [%0], %1;\n@p bra LD;\n"
               "nanosleep.u32 1000;\nadd.u32 n, n, 1;\nsetp.lt.u32 p, n, %2;\n@p bra LW;\ntrap;\nLD:\n}\n" ::"r"(a), "r"(par), "n"(SPIN_LIMIT) : "memory");
}
__device__ __forceinline__ void flag_wait(const unsigned* f, unsigned target) {
  asm volatile("{\n.reg .pred p;\n.reg .u32 n, v;\nmov.u32 n, 0;\n"
               "LW:\nld.acquire.gpu.global.u32 v, [%0];\nsub.u32 v, v, %1;\nsetp.ge.s32 p, v, 0;\n@p bra LD;\n"
               "add.u32 n, n, 1;\nsetp.lt.u32 p, n, %2;\n@p bra LW;\ntrap;\nLD:\n}\n" ::"l"(f), "r"(target), "n"(SPIN_LIMIT) : "memory");
}
__device__ __forceinline__ bool elect_one() {
  uint32_t r;
  asm volatile("{\n.reg .pred p;\nelect.sync _|p, 0xffffffff;\nselp.u32 %0, 1, 0, p;\n}\n" : "=r"(r));
  return r != 0;
}
__device__ __forceinline__ void flag_publish(unsigned* f) {
  asm volatile("fence.release.gpu;" ::: "memory");
  asm volatile("red.relaxed.gpu.global.add.u32 [%0], 1;" ::"l"(f) : "memory");
}
__device__ __forceinline__ void bar_sync(int id, int n) { asm volatile("bar.sync %0, %1;" ::"r"(id), "r"(n) : "memory"); }
__device__ __forceinline__ void bar_arrive(int id, int n) { asm volatile("bar.arrive %0, %1;" ::"r"(id), "r"(n) : "memory"); }
__device__ __forceinline__ void fence_async_smem() { asm volatile("fence.proxy.async.shared::cta;" ::: "memory"); }
__device__ __forceinline__ void fence_async_all() { asm volatile("fence.proxy.async.global;" ::: "memory"); }
__device__ __forceinline__ void wg_fence() { asm volatile("wgmma.fence.sync.aligned;" ::: "memory"); }
__device__ __forceinline__ void wg_commit() { asm volatile("wgmma.commit_group.sync.aligned;" ::: "memory"); }
template <int N> __device__ __forceinline__ void wg_wait() { asm volatile("wgmma.wait_group.sync.aligned %0;" ::"n"(N) : "memory"); }

__device__ __forceinline__ void bulk_g2s(uint32_t dst, const void* src, uint32_t bytes, uint32_t bar) {
  asm volatile("cp.async.bulk.shared::cluster.global.mbarrier::complete_tx::bytes [%0], [%1], %2, [%3];" ::"r"(dst), "l"(src), "r"(bytes), "r"(bar) : "memory");
}
__device__ __forceinline__ void tma_2d(uint32_t dst, const CUtensorMap* m, int c0, int c1, uint32_t bar) {
  asm volatile("cp.async.bulk.tensor.2d.shared::cluster.global.mbarrier::complete_tx::bytes [%0], [%1, {%2, %3}], [%4];"
               ::"r"(dst), "l"(m), "r"(c0), "r"(c1), "r"(bar) : "memory");
}
__device__ __forceinline__ void tma_4d(uint32_t dst, const CUtensorMap* m, int c0, int c1, int c2, int c3, uint32_t bar) {
  asm volatile("cp.async.bulk.tensor.4d.shared::cluster.global.mbarrier::complete_tx::bytes [%0], [%1, {%2, %3, %4, %5}], [%6];"
               ::"r"(dst), "l"(m), "r"(c0), "r"(c1), "r"(c2), "r"(c3), "r"(bar) : "memory");
}
__device__ __forceinline__ void tma_3d(uint32_t dst, const CUtensorMap* m, int c0, int c1, int c2, uint32_t bar) {
  asm volatile("cp.async.bulk.tensor.3d.shared::cluster.global.mbarrier::complete_tx::bytes [%0], [%1, {%2, %3, %4}], [%5];"
               ::"r"(dst), "l"(m), "r"(c0), "r"(c1), "r"(c2), "r"(bar) : "memory");
}
__device__ __forceinline__ void tmap_prefetch(const CUtensorMap* m) { asm volatile("prefetch.tensormap [%0];" ::"l"(m) : "memory"); }

template <class T> __device__ __forceinline__ T* sptr(uint32_t a) { return reinterpret_cast<T*>(__cvta_shared_to_generic(a)); }
__device__ __forceinline__ uint32_t lds32(uint32_t a) { return *sptr<const uint32_t>(a); }
__device__ __forceinline__ float ldsf(uint32_t a) { return *sptr<const float>(a); }
__device__ __forceinline__ float2 ldsf2(uint32_t a) { return *sptr<const float2>(a); }
__device__ __forceinline__ uint4 lds128(uint32_t a) { return *sptr<const uint4>(a); }
__device__ __forceinline__ void sts32(uint32_t a, uint32_t v) { *sptr<uint32_t>(a) = v; }
__device__ __forceinline__ void stsf(uint32_t a, float v) { *sptr<float>(a) = v; }
__device__ __forceinline__ void stsf2(uint32_t a, float x, float y) { *sptr<float2>(a) = make_float2(x, y); }
__device__ __forceinline__ void sts128(uint32_t a, uint4 v) { *sptr<uint4>(a) = v; }
__device__ __forceinline__ void ldsm4t(uint32_t a, uint32_t& r0, uint32_t& r1, uint32_t& r2, uint32_t& r3) {
  asm volatile("ldmatrix.sync.aligned.m8n8.x4.trans.shared.b16 {%0, %1, %2, %3}, [%4];" : "=r"(r0), "=r"(r1), "=r"(r2), "=r"(r3) : "r"(a) : "memory");
}
__device__ __forceinline__ void ldsm4(uint32_t a, uint32_t& r0, uint32_t& r1, uint32_t& r2, uint32_t& r3) {
  asm volatile("ldmatrix.sync.aligned.m8n8.x4.shared.b16 {%0, %1, %2, %3}, [%4];" : "=r"(r0), "=r"(r1), "=r"(r2), "=r"(r3) : "r"(a) : "memory");
}
__device__ __forceinline__ void stsm4(uint32_t a, uint32_t r0, uint32_t r1, uint32_t r2, uint32_t r3) {
  asm volatile("stmatrix.sync.aligned.m8n8.x4.shared.b16 [%0], {%1, %2, %3, %4};" ::"r"(a), "r"(r0), "r"(r1), "r"(r2), "r"(r3) : "memory");
}
__device__ __forceinline__ void stsm4t(uint32_t a, uint32_t r0, uint32_t r1, uint32_t r2, uint32_t r3) {
  asm volatile("stmatrix.sync.aligned.m8n8.x4.trans.shared.b16 [%0], {%1, %2, %3, %4};" ::"r"(a), "r"(r0), "r"(r1), "r"(r2), "r"(r3) : "memory");
}
__device__ __forceinline__ uint2 ldg64_nc(const void* p) { uint2 v; asm volatile("ld.global.nc.v2.b32 {%0, %1}, [%2];" : "=r"(v.x), "=r"(v.y) : "l"(p)); return v; }
__device__ __forceinline__ uint4 ldg128_nc(const void* p) { uint4 v; asm volatile("ld.global.nc.v4.b32 {%0, %1, %2, %3}, [%4];" : "=r"(v.x), "=r"(v.y), "=r"(v.z), "=r"(v.w) : "l"(p)); return v; }

__device__ __forceinline__ float bf_lo(uint32_t v) { return __uint_as_float(v << 16); }
__device__ __forceinline__ float bf_hi(uint32_t v) { return __uint_as_float(v & 0xffff0000u); }
__device__ __forceinline__ uint32_t pack_bf(float lo, float hi) { uint32_t r; asm("cvt.rn.bf16x2.f32 %0, %1, %2;" : "=r"(r) : "f"(hi), "f"(lo)); return r; }
__device__ __forceinline__ uint32_t pack_h(float lo, float hi) { uint32_t r; asm("cvt.rn.f16x2.f32 %0, %1, %2;" : "=r"(r) : "f"(hi), "f"(lo)); return r; }
__device__ __forceinline__ uint32_t bf2_add(uint32_t a, uint32_t b) { uint32_t r; asm("add.rn.bf16x2 %0, %1, %2;" : "=r"(r) : "r"(a), "r"(b)); return r; }
__device__ __forceinline__ uint32_t bf2_sub(uint32_t a, uint32_t b) { uint32_t r; asm("sub.rn.bf16x2 %0, %1, %2;" : "=r"(r) : "r"(a), "r"(b)); return r; }
__device__ __forceinline__ float bf_round(float x) { return bf_lo(pack_bf(x, 0.f)); }
__device__ __forceinline__ float2 unpack_h(uint32_t v) { return __half22float2(*reinterpret_cast<const __half2*>(&v)); }
__device__ __forceinline__ float ex2f(float x) { float y; asm("ex2.approx.ftz.f32 %0, %1;" : "=f"(y) : "f"(x)); return y; }
__device__ __forceinline__ float rcpf(float x) { float y; asm("rcp.approx.ftz.f32 %0, %1;" : "=f"(y) : "f"(x)); return y; }
__device__ __forceinline__ float bf2f(bf16 v) { return __bfloat162float(v); }

template <int N> __device__ __forceinline__ void pin_regs(float (&a)[N]) {
#pragma unroll
  for (int i = 0; i < N; i++) asm volatile("" : "+f"(a[i])::"memory");
}

__device__ __forceinline__ uint32_t g2_stage_off(uint32_t st) { return ((st & 1) ? SM_WR : 0) + (st >> 1) * G2_STAGE; }
__device__ __forceinline__ uint32_t desc_lo(uint32_t addr, uint32_t lbo) { return ((addr & 0x3FFFF) >> 4) | ((lbo >> 4) << 16); }

__device__ __forceinline__ float2 ln_finalize(float sum, float sq) {
  const float mean = sum * (1.0f / DM);
  const float var = fmaxf(fmaf(-mean, mean, sq * (1.0f / DM)), 0.f);
  const float ve = bf_round(bf_round(var) + 1e-5f);
  float s;
  asm("sqrt.approx.ftz.f32 %0, %1;" : "=f"(s) : "f"(ve));
  return make_float2(bf_round(mean), rcpf(bf_round(s)));
}

__device__ __forceinline__ void wg_g1_n128(float (&d)[64], uint32_t da, uint32_t db, int scale_d) {
  asm volatile("{\n.reg .pred p;\n.reg .b64 da, db;\n.reg .b32 ha, hb;\nsetp.ne.b32 p, %66, 0;\n"
    "mov.b32 ha, 1073741888;\nmov.b32 hb, 1073741888;\nmov.b64 da, {%64, ha};\nmov.b64 db, {%65, hb};\n"
    "wgmma.mma_async.sync.aligned.m64n128k16.f32.bf16.bf16 "
    "{%0, %1, %2, %3, %4, %5, %6, %7, %8, %9, %10, %11, %12, %13, %14, %15, %16, %17, %18, %19, %20, %21, %22, %23, %24, %25, %26, %27, %28, %29, %30, %31, %32, %33, %34, %35, %36, %37, %38, %39, %40, %41, %42, %43, %44, %45, %46, %47, %48, %49, %50, %51, %52, %53, %54, %55, %56, %57, %58, %59, %60, %61, %62, %63}, "
    "da, db, p, 1, 1, 1, 1;\n}\n"
    : "+f"(d[0]), "+f"(d[1]), "+f"(d[2]), "+f"(d[3]), "+f"(d[4]), "+f"(d[5]), "+f"(d[6]), "+f"(d[7]), "+f"(d[8]), "+f"(d[9]), "+f"(d[10]), "+f"(d[11]), "+f"(d[12]), "+f"(d[13]), "+f"(d[14]), "+f"(d[15]), "+f"(d[16]), "+f"(d[17]), "+f"(d[18]), "+f"(d[19]), "+f"(d[20]), "+f"(d[21]), "+f"(d[22]), "+f"(d[23]), "+f"(d[24]), "+f"(d[25]), "+f"(d[26]), "+f"(d[27]), "+f"(d[28]), "+f"(d[29]), "+f"(d[30]), "+f"(d[31]), "+f"(d[32]), "+f"(d[33]), "+f"(d[34]), "+f"(d[35]), "+f"(d[36]), "+f"(d[37]), "+f"(d[38]), "+f"(d[39]), "+f"(d[40]), "+f"(d[41]), "+f"(d[42]), "+f"(d[43]), "+f"(d[44]), "+f"(d[45]), "+f"(d[46]), "+f"(d[47]), "+f"(d[48]), "+f"(d[49]), "+f"(d[50]), "+f"(d[51]), "+f"(d[52]), "+f"(d[53]), "+f"(d[54]), "+f"(d[55]), "+f"(d[56]), "+f"(d[57]), "+f"(d[58]), "+f"(d[59]), "+f"(d[60]), "+f"(d[61]), "+f"(d[62]), "+f"(d[63])
    : "r"(da), "r"(db), "r"(scale_d));
}
__device__ __forceinline__ void wg_g1_n112(float (&d)[64], uint32_t da, uint32_t db, int scale_d) {
  asm volatile("{\n.reg .pred p;\n.reg .b64 da, db;\n.reg .b32 ha, hb;\nsetp.ne.b32 p, %58, 0;\n"
    "mov.b32 ha, 1073741888;\nmov.b32 hb, 1073741888;\nmov.b64 da, {%56, ha};\nmov.b64 db, {%57, hb};\n"
    "wgmma.mma_async.sync.aligned.m64n112k16.f32.bf16.bf16 "
    "{%0, %1, %2, %3, %4, %5, %6, %7, %8, %9, %10, %11, %12, %13, %14, %15, %16, %17, %18, %19, %20, %21, %22, %23, %24, %25, %26, %27, %28, %29, %30, %31, %32, %33, %34, %35, %36, %37, %38, %39, %40, %41, %42, %43, %44, %45, %46, %47, %48, %49, %50, %51, %52, %53, %54, %55}, "
    "da, db, p, 1, 1, 1, 1;\n}\n"
    : "+f"(d[0]), "+f"(d[1]), "+f"(d[2]), "+f"(d[3]), "+f"(d[4]), "+f"(d[5]), "+f"(d[6]), "+f"(d[7]), "+f"(d[8]), "+f"(d[9]), "+f"(d[10]), "+f"(d[11]), "+f"(d[12]), "+f"(d[13]), "+f"(d[14]), "+f"(d[15]), "+f"(d[16]), "+f"(d[17]), "+f"(d[18]), "+f"(d[19]), "+f"(d[20]), "+f"(d[21]), "+f"(d[22]), "+f"(d[23]), "+f"(d[24]), "+f"(d[25]), "+f"(d[26]), "+f"(d[27]), "+f"(d[28]), "+f"(d[29]), "+f"(d[30]), "+f"(d[31]), "+f"(d[32]), "+f"(d[33]), "+f"(d[34]), "+f"(d[35]), "+f"(d[36]), "+f"(d[37]), "+f"(d[38]), "+f"(d[39]), "+f"(d[40]), "+f"(d[41]), "+f"(d[42]), "+f"(d[43]), "+f"(d[44]), "+f"(d[45]), "+f"(d[46]), "+f"(d[47]), "+f"(d[48]), "+f"(d[49]), "+f"(d[50]), "+f"(d[51]), "+f"(d[52]), "+f"(d[53]), "+f"(d[54]), "+f"(d[55])
    : "r"(da), "r"(db), "r"(scale_d));
}
__device__ __forceinline__ void wg_g2_n64(float (&d)[32], uint32_t da, uint32_t db, int scale_d) {
  asm volatile("{\n.reg .pred p;\n.reg .b64 da, db;\n.reg .b32 ha, hb;\nsetp.ne.b32 p, %34, 0;\n"
    "mov.b32 ha, 1073741888;\nmov.b32 hb, 8;\nmov.b64 da, {%32, ha};\nmov.b64 db, {%33, hb};\n"
    "wgmma.mma_async.sync.aligned.m64n64k16.f32.bf16.bf16 "
    "{%0, %1, %2, %3, %4, %5, %6, %7, %8, %9, %10, %11, %12, %13, %14, %15, %16, %17, %18, %19, %20, %21, %22, %23, %24, %25, %26, %27, %28, %29, %30, %31}, "
    "da, db, p, 1, 1, 1, 0;\n}\n"
    : "+f"(d[0]), "+f"(d[1]), "+f"(d[2]), "+f"(d[3]), "+f"(d[4]), "+f"(d[5]), "+f"(d[6]), "+f"(d[7]), "+f"(d[8]), "+f"(d[9]), "+f"(d[10]), "+f"(d[11]), "+f"(d[12]), "+f"(d[13]), "+f"(d[14]), "+f"(d[15]), "+f"(d[16]), "+f"(d[17]), "+f"(d[18]), "+f"(d[19]), "+f"(d[20]), "+f"(d[21]), "+f"(d[22]), "+f"(d[23]), "+f"(d[24]), "+f"(d[25]), "+f"(d[26]), "+f"(d[27]), "+f"(d[28]), "+f"(d[29]), "+f"(d[30]), "+f"(d[31])
    : "r"(da), "r"(db), "r"(scale_d));
}
__device__ __forceinline__ void wg_kg_n48(float (&d)[24], uint32_t da, uint32_t db, int scale_d) {
  asm volatile("{\n.reg .pred p;\n.reg .b64 da, db;\n.reg .b32 ha, hb;\nsetp.ne.b32 p, %26, 0;\n"
    "mov.b32 ha, 1073741888;\nmov.b32 hb, 1073741888;\nmov.b64 da, {%24, ha};\nmov.b64 db, {%25, hb};\n"
    "wgmma.mma_async.sync.aligned.m64n48k16.f32.f16.f16 "
    "{%0, %1, %2, %3, %4, %5, %6, %7, %8, %9, %10, %11, %12, %13, %14, %15, %16, %17, %18, %19, %20, %21, %22, %23}, "
    "da, db, p, 1, 1, 0, 0;\n}\n"
    : "+f"(d[0]), "+f"(d[1]), "+f"(d[2]), "+f"(d[3]), "+f"(d[4]), "+f"(d[5]), "+f"(d[6]), "+f"(d[7]), "+f"(d[8]), "+f"(d[9]), "+f"(d[10]), "+f"(d[11]), "+f"(d[12]), "+f"(d[13]), "+f"(d[14]), "+f"(d[15]), "+f"(d[16]), "+f"(d[17]), "+f"(d[18]), "+f"(d[19]), "+f"(d[20]), "+f"(d[21]), "+f"(d[22]), "+f"(d[23])
    : "r"(da), "r"(db), "r"(scale_d));
}
__device__ __forceinline__ void wg_cv_n64(float (&d)[32], uint32_t a0, uint32_t a1, uint32_t a2, uint32_t a3, uint32_t db, int scale_d) {
  asm volatile("{\n.reg .pred p;\n.reg .b64 db;\n.reg .b32 hb;\nsetp.ne.b32 p, %37, 0;\n"
    "mov.b32 hb, 2147483680;\nmov.b64 db, {%36, hb};\n"
    "wgmma.mma_async.sync.aligned.m64n64k16.f32.f16.f16 "
    "{%0, %1, %2, %3, %4, %5, %6, %7, %8, %9, %10, %11, %12, %13, %14, %15, %16, %17, %18, %19, %20, %21, %22, %23, %24, %25, %26, %27, %28, %29, %30, %31}, "
    "{%32, %33, %34, %35}, db, p, 1, 1, 0;\n}\n"
    : "+f"(d[0]), "+f"(d[1]), "+f"(d[2]), "+f"(d[3]), "+f"(d[4]), "+f"(d[5]), "+f"(d[6]), "+f"(d[7]), "+f"(d[8]), "+f"(d[9]), "+f"(d[10]), "+f"(d[11]), "+f"(d[12]), "+f"(d[13]), "+f"(d[14]), "+f"(d[15]), "+f"(d[16]), "+f"(d[17]), "+f"(d[18]), "+f"(d[19]), "+f"(d[20]), "+f"(d[21]), "+f"(d[22]), "+f"(d[23]), "+f"(d[24]), "+f"(d[25]), "+f"(d[26]), "+f"(d[27]), "+f"(d[28]), "+f"(d[29]), "+f"(d[30]), "+f"(d[31])
    : "r"(a0), "r"(a1), "r"(a2), "r"(a3), "r"(db), "r"(scale_d));
}
__device__ __forceinline__ void wg_cv_n56(float (&d)[28], uint32_t a0, uint32_t a1, uint32_t a2, uint32_t a3, uint32_t db, int scale_d) {
  asm volatile("{\n.reg .pred p;\n.reg .b64 db;\n.reg .b32 hb;\nsetp.ne.b32 p, %33, 0;\n"
    "mov.b32 hb, 2147483680;\nmov.b64 db, {%32, hb};\n"
    "wgmma.mma_async.sync.aligned.m64n56k16.f32.f16.f16 "
    "{%0, %1, %2, %3, %4, %5, %6, %7, %8, %9, %10, %11, %12, %13, %14, %15, %16, %17, %18, %19, %20, %21, %22, %23, %24, %25, %26, %27}, "
    "{%28, %29, %30, %31}, db, p, 1, 1, 0;\n}\n"
    : "+f"(d[0]), "+f"(d[1]), "+f"(d[2]), "+f"(d[3]), "+f"(d[4]), "+f"(d[5]), "+f"(d[6]), "+f"(d[7]), "+f"(d[8]), "+f"(d[9]), "+f"(d[10]), "+f"(d[11]), "+f"(d[12]), "+f"(d[13]), "+f"(d[14]), "+f"(d[15]), "+f"(d[16]), "+f"(d[17]), "+f"(d[18]), "+f"(d[19]), "+f"(d[20]), "+f"(d[21]), "+f"(d[22]), "+f"(d[23]), "+f"(d[24]), "+f"(d[25]), "+f"(d[26]), "+f"(d[27])
    : "r"(a0), "r"(a1), "r"(a2), "r"(a3), "r"(db), "r"(scale_d));
}
__device__ __forceinline__ void wg_cv_n40(float (&d)[20], uint32_t a0, uint32_t a1, uint32_t a2, uint32_t a3, uint32_t db, int scale_d) {
  asm volatile("{\n.reg .pred p;\n.reg .b64 db;\n.reg .b32 hb;\nsetp.ne.b32 p, %25, 0;\n"
    "mov.b32 hb, 2147483680;\nmov.b64 db, {%24, hb};\n"
    "wgmma.mma_async.sync.aligned.m64n40k16.f32.f16.f16 "
    "{%0, %1, %2, %3, %4, %5, %6, %7, %8, %9, %10, %11, %12, %13, %14, %15, %16, %17, %18, %19}, "
    "{%20, %21, %22, %23}, db, p, 1, 1, 0;\n}\n"
    : "+f"(d[0]), "+f"(d[1]), "+f"(d[2]), "+f"(d[3]), "+f"(d[4]), "+f"(d[5]), "+f"(d[6]), "+f"(d[7]), "+f"(d[8]), "+f"(d[9]), "+f"(d[10]), "+f"(d[11]), "+f"(d[12]), "+f"(d[13]), "+f"(d[14]), "+f"(d[15]), "+f"(d[16]), "+f"(d[17]), "+f"(d[18]), "+f"(d[19])
    : "r"(a0), "r"(a1), "r"(a2), "r"(a3), "r"(db), "r"(scale_d));
}
__device__ __forceinline__ void wg_cv_n16t(float (&d)[8], uint32_t a0, uint32_t a1, uint32_t a2, uint32_t a3, uint32_t db, int scale_d) {
  asm volatile("{\n.reg .pred p;\n.reg .b64 db;\n.reg .b32 hb;\nsetp.ne.b32 p, %13, 0;\n"
    "mov.b32 hb, 3221225488;\nmov.b64 db, {%12, hb};\n"
    "wgmma.mma_async.sync.aligned.m64n16k16.f32.f16.f16 "
    "{%0, %1, %2, %3, %4, %5, %6, %7}, "
    "{%8, %9, %10, %11}, db, p, 1, 1, 1;\n}\n"
    : "+f"(d[0]), "+f"(d[1]), "+f"(d[2]), "+f"(d[3]), "+f"(d[4]), "+f"(d[5]), "+f"(d[6]), "+f"(d[7])
    : "r"(a0), "r"(a1), "r"(a2), "r"(a3), "r"(db), "r"(scale_d));
}

__device__ __forceinline__ float2 cmul(float2 a, float2 b) {
  return make_float2(fmaf(a.x, b.x, -a.y * b.y), fmaf(a.x, b.y, a.y * b.x));
}
__device__ __forceinline__ float2 cexp_p(float ar, float ai, float p) {
  float xr = ar * p, xi = ai * p;
  float mag = ex2f(xr * 1.4426950408889634f);
  float k = rintf(xi * 0.15915494309189535f);
  float r = fmaf(-k, 6.2831854820251465f, xi);
  r = fmaf(-k, -1.7484555314695172e-07f, r);
  float s, c;
  __sincosf(r, &s, &c);
  return make_float2(mag * c, mag * s);
}
__device__ __forceinline__ int pos_index(int j) {
  int b = (int)(pack_bf((float)j, 0.f) & 0xffffu) - 17024;
  return j < 128 ? j : b;
}

struct KParam { float logA, aim, cre, cim, logdt; };

__device__ __forceinline__ void kgen(uint32_t sb, int w, int wp, int lane, const KParam (&kp)[2], float (&kinv)[2], const bf16* xsrc) {
  uint2 xr[8];
  const int t = wp * 32 + lane;
  float ar[2], ai[2];
  float2 C[2];
  const uint32_t mxa = sb + SM_MISC + 12288 + w * 32;
#pragma unroll
  for (int v = 0; v < 2; v++) {
    const float dt = bf_round(expf(kp[v].logdt));
    const float lar = -bf_round(expf(kp[v].logA));
    ar[v] = lar * dt; ai[v] = kp[v].aim * dt;
    C[v] = make_float2(kp[v].cre * dt, kp[v].cim * dt);
    float mx = fmaxf(fabsf(C[v].x), fabsf(C[v].y));
#pragma unroll
    for (int o = 16; o; o >>= 1) mx = fmaxf(mx, __shfl_xor_sync(0xffffffffu, mx, o));
    if (lane == 0) stsf(mxa + v * 16 + wp * 4, mx);
  }
  bar_sync(1 + w, 128);
#pragma unroll
  for (int v = 0; v < 2; v++) {
    const uint4 m4 = lds128(mxa + v * 16);
    const float mx = fmaxf(fmaxf(__uint_as_float(m4.x), __uint_as_float(m4.y)), fmaxf(__uint_as_float(m4.z), __uint_as_float(m4.w)));
    int e = (__float_as_uint(mx) >> 23) & 255;
    e = min(max(e, 4), 254);
    const float scale2 = __uint_as_float((uint32_t)(258 - e) << 23);
    kinv[v] = __uint_as_float((uint32_t)(e - 3) << 23);
    C[v].x *= scale2; C[v].y *= scale2;
  }
  const uint32_t ga = sb + KG_B + w * 57344 + wp * 6144 + lane * 4;
  const uint32_t fa = sb + KG_A + w * 57344 + wp * 8192 + lane * 4;
  auto putG = [&](int v, int h, float2 g) { sts32((ga ^ ((h & 7) << 4)) + (24 * v + h) * 128, pack_h(g.x, -g.y)); };
  float2 E8[2];
#pragma unroll
  for (int v = 0; v < 2; v++) {
    const float2 E1 = cexp_p(ar[v], ai[v], 1.f), E256 = cexp_p(ar[v], ai[v], 256.f);
    const float2 E2 = cmul(E1, E1), E4 = cmul(E2, E2), E512 = cmul(E256, E256), E1024 = cmul(E512, E512);
    E8[v] = cmul(E4, E4);
    {
      float2 g0 = C[v], g1 = cmul(C[v], E1);
      putG(v, 0, g0); putG(v, 1, g1);
#pragma unroll
      for (int h = 2; h < 8; h += 2) { g0 = cmul(g0, E2); g1 = cmul(g1, E2); putG(v, h, g0); putG(v, h + 1, g1); }
      xr[4 * v] = ldg64_nc(xsrc + (4 * v) * DM);
    }
    {
      const float2 g = cmul(C[v], E256), g4 = cmul(g, E4);
      putG(v, 8, g); putG(v, 9, cmul(g, E2)); putG(v, 10, g4); putG(v, 11, cmul(g4, E2));
      xr[4 * v + 1] = ldg64_nc(xsrc + (4 * v + 1) * DM);
    }
    {
      const float2 g = cmul(C[v], E512), g2 = cmul(g, E256);
      putG(v, 12, g); putG(v, 13, cmul(g, E4)); putG(v, 14, g2); putG(v, 15, cmul(g2, E4));
      xr[4 * v + 2] = ldg64_nc(xsrc + (4 * v + 2) * DM);
    }
    {
      const float2 g = cmul(C[v], E1024), g2 = cmul(g, E512);
      putG(v, 16, g); putG(v, 17, cmul(g, E256)); putG(v, 18, g2); putG(v, 19, cmul(g2, E256)); putG(v, 20, cmul(g, E1024));
      xr[4 * v + 3] = ldg64_nc(xsrc + (4 * v + 3) * DM);
    }
  }
  {
    float2 f[2][2], E16[2];
#pragma unroll
    for (int v = 0; v < 2; v++) { E16[v] = cmul(E8[v], E8[v]); f[v][0] = make_float2(1.f, 0.f); f[v][1] = E8[v]; }
#pragma unroll 2
    for (int o = 0; o < 32; o += 2) {
      const uint32_t a0 = (fa ^ ((o & 7) << 4)) + o * 128, a1 = (fa ^ (((o + 1) & 7) << 4)) + (o + 1) * 128;
#pragma unroll
      for (int v = 0; v < 2; v++) {
        sts32(a0 + v * 4096, pack_h(f[v][0].x, f[v][0].y));
        sts32(a1 + v * 4096, pack_h(f[v][1].x, f[v][1].y));
        f[v][0] = cmul(f[v][0], E16[v]); f[v][1] = cmul(f[v][1], E16[v]);
      }
    }
  }
  fence_async_smem();
  bar_sync(1 + w, 128);
  float acc[24];
#pragma unroll
  for (int i = 0; i < 24; i++) acc[i] = 0.f;
  pin_regs(acc);
  {
    const uint32_t da = desc_lo(sb + KG_A + w * 57344, 16), db = desc_lo(sb + KG_B + w * 57344, 16);
    wg_fence();
#pragma unroll
    for (int kb = 0; kb < 4; kb++) {
#pragma unroll
      for (int k = 0; k < 4; k++) wg_kg_n48(acc, da + kb * 512 + k * 2, db + kb * 384 + k * 2, (kb | k) != 0);
    }
    wg_commit();
    {
      uint4 a, b, c, d;
      a.x = __byte_perm(xr[0].x, xr[1].x, 0x5410); b.x = __byte_perm(xr[0].x, xr[1].x, 0x7632);
      a.y = __byte_perm(xr[2].x, xr[3].x, 0x5410); b.y = __byte_perm(xr[2].x, xr[3].x, 0x7632);
      a.z = __byte_perm(xr[4].x, xr[5].x, 0x5410); b.z = __byte_perm(xr[4].x, xr[5].x, 0x7632);
      a.w = __byte_perm(xr[6].x, xr[7].x, 0x5410); b.w = __byte_perm(xr[6].x, xr[7].x, 0x7632);
      c.x = __byte_perm(xr[0].y, xr[1].y, 0x5410); d.x = __byte_perm(xr[0].y, xr[1].y, 0x7632);
      c.y = __byte_perm(xr[2].y, xr[3].y, 0x5410); d.y = __byte_perm(xr[2].y, xr[3].y, 0x7632);
      c.z = __byte_perm(xr[4].y, xr[5].y, 0x5410); d.z = __byte_perm(xr[4].y, xr[5].y, 0x7632);
      c.w = __byte_perm(xr[6].y, xr[7].y, 0x5410); d.w = __byte_perm(xr[6].y, xr[7].y, 0x7632);
      const uint32_t xa = sb + CV_XS + (w * 128 + t) * 16;
      sts128(xa, a); sts128(xa + 4096, b); sts128(xa + 8192, c); sts128(xa + 12288, d);
    }
    wg_wait<0>();
    pin_regs(acc);
    if (lane == 0) mbar_arrive(sb + SM_BAR + 8 * B_KGDONE);
  }
  const uint32_t kt = sb + SM_MISC + w * 2592;
  {
    const int g = lane >> 2, c = lane & 3, v = wp >> 1;
    const uint32_t kv = kt + v * 5184;
#pragma unroll
    for (int hh = 0; hh < 2; hh++) {
      const int o = 16 * (wp & 1) + g + 8 * hh;
#pragma unroll
      for (int k = 0; k < 2; k++) {
        const float a0 = v ? acc[12 + 2 * hh + k] : acc[2 * hh + k];
        const float a1 = v ? acc[16 + 2 * hh + k] : acc[4 + 2 * hh + k];
        const float a2 = v ? acc[20 + 2 * hh + k] : acc[8 + 2 * hh + k];
        stsf(kv + (2 * c + k + 8 * o) * 4, a0);
        stsf(kv + (c < 2 ? 256 + 2 * c + k + 4 * o : 384 + 64 * (c - 2) + k + 2 * o) * 4, a1);
        if (c < 2) stsf(kv + (512 + 32 * (2 * c + k) + o) * 4, a2);
        else if (c == 2 && k == 0 && o == 0) stsf(kv + 640 * 4, a2);
      }
    }
  }
  bar_sync(1 + w, 128);
  const uint32_t pt = sb + SM_PT + w * (PTW * 4);
#pragma unroll 1
  for (int i = 0; i < 3; i++) {
    const int q = t + 128 * i;
    if (q < PAW / 4) {
      const int x0 = 4 * q - 65;
      float kv[2][5];
#pragma unroll
      for (int k = 0; k < 5; k++) {
        const int x = x0 + k;
        const bool ok = x >= 0 && x <= 1028;
        const uint32_t a = kt + (ok ? pos_index(x) : 0) * 4;
#pragma unroll
        for (int v = 0; v < 2; v++) { const float f = ldsf(a + v * 5184); kv[v][k] = ok ? f : 0.f; }
      }
#pragma unroll
      for (int v = 0; v < 2; v++)
        sts128(pt + v * (2 * PTW * 4) + q * 16, make_uint4(pack_h(kv[v][1], kv[v][0]), pack_h(kv[v][2], kv[v][1]), pack_h(kv[v][3], kv[v][2]), pack_h(kv[v][4], kv[v][3])));
    }
  }
  {
    const int z = t - 64;
#pragma unroll
    for (int v = 0; v < 2; v++) {
      const uint32_t k0 = kt + v * 5184 + 8 * max(z, 0);
      const float a = ldsf(k0 + 511 * 4), b = ldsf(k0 + 512 * 4), c = ldsf(k0 + 513 * 4), d = ldsf(k0 + 514 * 4);
      sts32(pt + v * (2 * PTW * 4) + (PAW + t) * 4, pack_h(z >= 0 ? d : 0.f, z >= 1 ? b : 0.f));
      sts32(pt + v * (2 * PTW * 4) + (PAW + 128 + t) * 4, pack_h(z >= 0 ? c : 0.f, z >= 1 ? a : 0.f));
    }
  }
  fence_async_smem();
  __syncwarp();
  if (lane == 0) mbar_arrive(sb + SM_BAR + 8 * B_PTDONE);
}

__device__ __forceinline__ void load_mu2(uint32_t (&q)[16], uint32_t a) {
#pragma unroll
  for (int h = 0; h < 2; h++) {
    q[8 * h + 2] = lds32(a + h * 256); q[8 * h] = lds32(a + h * 256 + 32); q[8 * h + 1] = lds32(a + h * 256 + 64);
    q[8 * h + 4] = lds32(a + h * 256 + 96); q[8 * h + 5] = lds32(a + h * 256 + 128);
  }
}
__device__ __forceinline__ void fix_mu(uint32_t (&q)[16], int h) { q[8 * h + 3] = q[8 * h]; q[8 * h + 6] = q[8 * h + 1]; q[8 * h + 7] = q[8 * h + 4]; }
#define MU2_GROUP(FN, ACC, Q, DB, SC0)                        \
  do {                                                        \
    fix_mu(Q, 0); fix_mu(Q, 1);                               \
    wg_fence();                                               \
    FN(ACC, Q[0], Q[1], Q[2], Q[3], (DB) + 2, SC0);           \
    FN(ACC, Q[4], Q[5], Q[6], Q[7], (DB), 1);                 \
    FN(ACC, Q[8], Q[9], Q[10], Q[11], (DB) - 8 + 2, 1);       \
    FN(ACC, Q[12], Q[13], Q[14], Q[15], (DB) - 8, 1);         \
    wg_commit();                                              \
  } while (0)
__device__ __forceinline__ void load_far(uint32_t (&q)[16], uint32_t a) {
  q[2] = lds32(a);
#pragma unroll
  for (int k = 0; k < 4; k++) { q[4 * k] = lds32(a + (2 * k + 1) * 32); q[4 * k + 1] = lds32(a + (2 * k + 2) * 32); }
}
#define FAR_GROUP(ACC, Q, DB, SC0)                                                        \
  do {                                                                                    \
    _Pragma("unroll") for (int k = 0; k < 4; k++) { Q[4 * k + 3] = Q[4 * k]; if (k) Q[4 * k + 2] = Q[4 * k - 3]; } \
    wg_fence();                                                                           \
    wg_cv_n16t(ACC, Q[0], Q[1], Q[2], Q[3], (DB) + 96, SC0);                              \
    wg_cv_n16t(ACC, Q[4], Q[5], Q[6], Q[7], (DB) + 64, 1);                                \
    wg_cv_n16t(ACC, Q[8], Q[9], Q[10], Q[11], (DB) + 32, 1);                              \
    wg_cv_n16t(ACC, Q[12], Q[13], Q[14], Q[15], (DB), 1);                                 \
    wg_commit();                                                                          \
  } while (0)

__device__ __forceinline__ uint32_t u_chunk(uint32_t base, int q) {
  const int qq = q + 64, row = qq >> 2;
  return base + row * 64 + (((qq & 3) ^ ((row >> 1) & 3)) << 4);
}

__device__ __forceinline__ void conv_phase(const Params& p, uint32_t sb, int layer, int w, int wp, int lane, int cta,
                                           float kinvA, float kinvB) {
  const int t = wp * 32 + lane, T = w * 128 + t;
  const uint32_t bar = sb + SM_BAR;
  if (layer == 0) bar_sync(4, 256);
  sts128(sb + CV_U + (w + 2 * (t >> 6)) * 5120 + (t & 63) * 16, make_uint4(0, 0, 0, 0));
  mbar_wait(bar + 8 * B_XSFULL, layer);
  {
    uint4 v[4];
#pragma unroll
    for (int i = 0; i < 4; i++) v[i] = lds128(sb + CV_B97 + T * 64 + i * 16);
    const uint32_t sa = sb + SM_STAT + (T >> 1) * 16 + (T & 1) * 8192;
#pragma unroll
    for (int i = 0; i < 4; i++) {
      const float2 a = ln_finalize(__uint_as_float(v[i].x), __uint_as_float(v[i].y));
      const float2 b = ln_finalize(__uint_as_float(v[i].z), __uint_as_float(v[i].w));
      sts128(sa + i * 2048, make_uint4(__byte_perm(__float_as_uint(a.x), __float_as_uint(b.x), 0x7632), __float_as_uint(a.y), __float_as_uint(b.y), 0));
    }
    bar_sync(4, 256);
  }
  {
    uint4 st[8], x[4];
#pragma unroll
    for (int i = 0; i < 8; i++) st[i] = lds128(sb + SM_STAT + t * 16 + i * 2048);
#pragma unroll
    for (int i = 0; i < 4; i++) x[i] = lds128(sb + CV_XS + (w + 2 * (i >> 1)) * 4096 + t * 32 + (i & 1) * 16);
#pragma unroll
    for (int i = 0; i < 4; i++) {
      const uint32_t xx[4] = {x[i].x, x[i].y, x[i].z, x[i].w};
      uint32_t hh[4];
#pragma unroll
      for (int k = 0; k < 4; k++) {
        const uint4 s4 = st[4 * (i & 1) + k];
        const uint32_t dd = bf2_sub(xx[k], s4.x);
        hh[k] = pack_h(bf_lo(dd) * __uint_as_float(s4.y), bf_hi(dd) * __uint_as_float(s4.z));
      }
      sts128(u_chunk(sb + CV_U + (w + 2 * (i >> 1)) * 5120, 2 * t + (i & 1)), make_uint4(hh[0], hh[1], hh[2], hh[3]));
    }
  }
  fence_async_smem();
  bar_sync(4, 256);
  if (w == 1) {
#pragma unroll 1
    for (int h2 = 0; h2 < 2; h2++) {
      uint4 x[8];
#pragma unroll
      for (int k = 0; k < 8; k++) x[k] = lds128(u_chunk(sb + CV_U + (2 * h2 + (k >> 2)) * 5120, t - 3 + (k & 3)));
#pragma unroll
      for (int v = 0; v < 2; v++) {
        float u[32];
#pragma unroll
        for (int k = 0; k < 4; k++) {
          float2 f;
          f = unpack_h(x[4 * v + k].x); u[8 * k] = f.x; u[8 * k + 1] = f.y;
          f = unpack_h(x[4 * v + k].y); u[8 * k + 2] = f.x; u[8 * k + 3] = f.y;
          f = unpack_h(x[4 * v + k].z); u[8 * k + 4] = f.x; u[8 * k + 5] = f.y;
          f = unpack_h(x[4 * v + k].w); u[8 * k + 6] = f.x; u[8 * k + 7] = f.y;
        }
        float s9[8], s7[8];
        s9[0] = ((u[4] + u[5]) + (u[6] + u[7])) + ((u[8] + u[9]) + (u[10] + u[11])) + u[12];
        s9[4] = ((u[8] + u[9]) + (u[10] + u[11])) + ((u[12] + u[13]) + (u[14] + u[15])) + u[16];
        s7[0] = ((u[13] + u[14]) + (u[15] + u[16])) + ((u[17] + u[18]) + u[19]);
        s7[4] = ((u[17] + u[18]) + (u[19] + u[20])) + ((u[21] + u[22]) + u[23]);
#pragma unroll
        for (int j = 1; j < 4; j++) {
          s9[j] = s9[j - 1] + (u[j + 12] - u[j + 3]); s9[j + 4] = s9[j + 3] + (u[j + 16] - u[j + 7]);
          s7[j] = s7[j - 1] + (u[j + 19] - u[j + 12]); s7[j + 4] = s7[j + 3] + (u[j + 23] - u[j + 16]);
        }
        const uint32_t off = (uint32_t)(t * 16) ^ (((t >> 3) & 1) << 4);
        const uint32_t ba = sb + CV_B97 + (2 * h2 + v) * 4096 + off;
        sts128(ba, make_uint4(pack_h(s9[0], s9[1]), pack_h(s9[2], s9[3]), pack_h(s9[4], s9[5]), pack_h(s9[6], s9[7])));
        sts128(ba + 2048, make_uint4(pack_h(s7[0], s7[1]), pack_h(s7[2], s7[3]), pack_h(s7[4], s7[5]), pack_h(s7[6], s7[7])));
      }
    }
    fence_async_smem();
    __syncwarp();
    if (lane == 0) mbar_arrive(bar + 8 * B_B97);
  }
  if (layer != 0) mbar_wait(bar + 8 * B_PTFULL, 0);

  const int g = lane >> 2, c = lane & 3;
  bf16* xout = p.sc->xT[layer == 0 ? 0 : 2];
  const uint32_t ex = sb + (w ? CV_E0 : CV_E1), y3 = ex + 8192;
  float ps[16], pq[16];
#pragma unroll
  for (int i = 0; i < 16; i++) { ps[i] = 0.f; pq[i] = 0.f; }
#pragma unroll 1
  for (int v = 0; v < 2; v++) {
    const int slot = w + 2 * v, ch = 4 * cta + slot;
    const float dsk = bf2f(p.Dsk[ch]);
    const uint32_t pa = sb + SM_PT + slot * (PTW * 4) + (64 + 16 * wp + g - 2 * c) * 4;
    const uint32_t ub = sb + CV_U + slot * 5120;
    const uint32_t du = desc_lo(ub + 16 * 64, 16);
    const uint32_t d9 = desc_lo(sb + CV_B97 + slot * 4096, 2048);
    float acc1[32], acc2[28], acc4[20], acc3[8];
#pragma unroll
    for (int i = 0; i < 32; i++) acc1[i] = 0.f;
#pragma unroll
    for (int i = 0; i < 28; i++) acc2[i] = 0.f;
#pragma unroll
    for (int i = 0; i < 20; i++) acc4[i] = 0.f;
#pragma unroll
    for (int i = 0; i < 8; i++) acc3[i] = 0.f;
    pin_regs(acc1); pin_regs(acc2); pin_regs(acc4); pin_regs(acc3);
    uint32_t qa[16], qb[16], qc[16];
    load_mu2(qa, pa - 3 * 32);
    load_mu2(qb, pa - 3 * 32 + 512);
    MU2_GROUP(wg_cv_n64, acc1, qa, du, 0);
    load_mu2(qc, pa - 3 * 32 + 1024);
    MU2_GROUP(wg_cv_n64, acc1, qb, du - 16, 1);
    wg_wait<1>();
    load_mu2(qa, pa - 3 * 32 + 1536);
    MU2_GROUP(wg_cv_n64, acc1, qc, du - 32, 1);
    wg_wait<1>();
    load_mu2(qb, pa - 3 * 32 + 2048);
    MU2_GROUP(wg_cv_n56, acc2, qa, du + 32 - 48, 0);
    wg_wait<1>();
    load_mu2(qc, pa - 3 * 32 + 2560);
    MU2_GROUP(wg_cv_n56, acc2, qb, du + 32 - 64, 1);
    wg_wait<1>();
    load_mu2(qa, pa - 3 * 32 + 3072);
    MU2_GROUP(wg_cv_n56, acc2, qc, du + 32 - 80, 1);
    wg_wait<1>();
    load_mu2(qb, pa - 3 * 32 + 3584);
    MU2_GROUP(wg_cv_n40, acc4, qa, du + 96 - 96, 0);
    wg_wait<1>();
    qc[2] = lds32(pa - 96 + 4096); qc[0] = lds32(pa - 64 + 4096); qc[1] = lds32(pa - 32 + 4096); qc[4] = lds32(pa + 4096); qc[5] = lds32(pa + 32 + 4096);
    MU2_GROUP(wg_cv_n40, acc4, qb, du + 96 - 112, 1);
    wg_wait<1>();
    load_far(qa, pa + PAW * 4 - 7 * 32);
    fix_mu(qc, 0);
    wg_fence();
    wg_cv_n40(acc4, qc[0], qc[1], qc[2], qc[3], du + 96 - 128 + 2, 1);
    wg_cv_n40(acc4, qc[4], qc[5], qc[6], qc[7], du + 96 - 128, 1);
    wg_commit();
    wg_wait<1>();
    load_far(qb, pa + (PAW + 128) * 4 - 7 * 32);
    mbar_wait(bar + 8 * B_B97, layer);
    FAR_GROUP(acc3, qa, d9, 0);
    FAR_GROUP(acc3, qb, d9 + (2048 >> 4), 1);
    wg_wait<0>();
    pin_regs(acc1); pin_regs(acc2); pin_regs(acc4); pin_regs(acc3);

#pragma unroll
    for (int i = 0; i < 28; i++) acc1[4 + i] += acc2[i];
#pragma unroll
    for (int i = 0; i < 20; i++) acc1[12 + i] += acc4[i];
    if (wp >= 2) {
      const int src = (lane & ~3) | ((c + 3) & 3);
#pragma unroll
      for (int nb = 7; nb >= 0; nb--)
#pragma unroll
        for (int hh = 0; hh < 2; hh++) {
          const float cur1 = acc1[4 * nb + 2 * hh + 1];
          const float prev1 = nb ? acc1[4 * (nb - 1) + 2 * hh + 1] : 0.f;
          const float sh = __shfl_sync(0xffffffffu, c == 3 ? prev1 : cur1, src);
          acc1[4 * nb + 2 * hh + 1] = acc1[4 * nb + 2 * hh];
          acc1[4 * nb + 2 * hh] = sh;
        }
    }
    {
      const uint32_t ea = ex + (wp >> 1) * 4096 + (wp & 1) * 2048 + lane * 8;
#pragma unroll
      for (int j = 0; j < 8; j++) {
        const float a = wp >= 2 ? acc1[2 * j] : acc1[16 + 2 * j], b = wp >= 2 ? acc1[2 * j + 1] : acc1[16 + 2 * j + 1];
        stsf2(ea + j * 256, a, b);
      }
#pragma unroll
      for (int nb = 0; nb < 2; nb++)
#pragma unroll
        for (int hh = 0; hh < 2; hh++) {
          const int z = 16 * (16 * wp + g + 8 * hh) + 8 * nb + 2 * c;
          stsf2(y3 + (z ^ (((z >> 6) & 3) << 3)) * 4, acc3[4 * nb + 2 * hh], acc3[4 * nb + 2 * hh + 1]);
        }
    }
    bar_sync(1 + w, 128);
    {
      const float kinv = v ? kinvB : kinvA;
      const int hi = wp >> 1, wq = wp & 1;
      float yv[16];
      const uint32_t ea = ex + (hi ^ 1) * 4096 + wq * 2048 + lane * 8;
#pragma unroll
      for (int j = 0; j < 8; j++) {
        const float2 e = ldsf2(ea + j * 256);
        yv[2 * j] = e.x + (hi ? acc1[16 + 2 * j] : acc1[2 * j]);
        yv[2 * j + 1] = e.y + (hi ? acc1[16 + 2 * j + 1] : acc1[2 * j + 1]);
      }
      if (hi) {
#pragma unroll
        for (int j = 0; j < 16; j++) {
          const int z = 32 * (8 * (j >> 2) + 2 * c + (j & 1)) + 16 * wq + g + 8 * ((j >> 1) & 1);
          yv[j] += ldsf(y3 + (z ^ (((z >> 6) & 3) << 3)) * 4);
        }
      }
      const int mat = lane >> 3, ib = 32 * hi + (lane & 7) + 8 * (mat >> 1), r8 = 2 * wq + (mat & 1);
      uint32_t xr[8], ur[8];
#pragma unroll
      for (int h2 = 0; h2 < 2; h2++) {
        const int i = ib + 16 * h2;
        ldsm4t(sb + CV_XS + slot * 4096 + i * 64 + r8 * 16, xr[4 * h2], xr[4 * h2 + 1], xr[4 * h2 + 2], xr[4 * h2 + 3]);
        ldsm4t(u_chunk(ub, 4 * i + r8), ur[4 * h2], ur[4 * h2 + 1], ur[4 * h2 + 2], ur[4 * h2 + 3]);
      }
      uint32_t o[8];
#pragma unroll
      for (int j = 0; j < 8; j++) {
        const uint32_t yy = pack_bf(yv[2 * j] * kinv, yv[2 * j + 1] * kinv);
        const float2 uf = unpack_h(ur[j]);
        o[j] = bf2_add(xr[j], bf2_add(yy, pack_bf(uf.x * dsk, uf.y * dsk)));
      }
      const uint32_t ob = sb + CV_B97 + slot * 4096;
#pragma unroll
      for (int h2 = 0; h2 < 2; h2++) {
        const int i = ib + 16 * h2;
        stsm4t(ob + i * 64 + ((r8 ^ ((i >> 1) & 3)) << 4), o[4 * h2], o[4 * h2 + 1], o[4 * h2 + 2], o[4 * h2 + 3]);
      }
      bar_sync(1 + w, 128);
      const int i = t >> 1, c0 = (t & 1) * 2;
      const uint4 o0 = lds128(ob + i * 64 + ((c0 ^ ((i >> 1) & 3)) << 4)), o1 = lds128(ob + i * 64 + (((c0 + 1) ^ ((i >> 1) & 3)) << 4));
      const int krow = 2 * (cta & 31) + w;
      char* dst = reinterpret_cast<char*>(xout) + (((t >> 3) * 8 + 4 * v + (cta >> 5)) * 2 + ((t >> 2) & 1)) * 8192 + krow * 128;
      *reinterpret_cast<uint4*>(dst + (((2 * (t & 3)) ^ (krow & 7)) << 4)) = o0;
      *reinterpret_cast<uint4*>(dst + (((2 * (t & 3) + 1) ^ (krow & 7)) << 4)) = o1;
      __syncwarp();
      if (lane == 0) mbar_arrive(bar + 8 * (B_PUB + 2 * w + v));
      const uint32_t oo[8] = {o0.x, o0.y, o0.z, o0.w, o1.x, o1.y, o1.z, o1.w};
#pragma unroll
      for (int k = 0; k < 8; k++) {
        const float lo = bf_lo(oo[k]), hi2 = bf_hi(oo[k]);
        ps[2 * k] += lo; pq[2 * k] = fmaf(lo, lo, pq[2 * k]);
        ps[2 * k + 1] += hi2; pq[2 * k + 1] = fmaf(hi2, hi2, pq[2 * k + 1]);
      }
    }
  }
  fence_async_smem();
  __syncwarp();
  if (lane == 0) mbar_arrive(bar + 8 * B_CONVDONE);
  const uint32_t sa = sb + SM_MISC + t * 128;
  if (w == 0) {
#pragma unroll
    for (int i = 0; i < 8; i++)
      sts128(sa + ((i ^ (t & 7)) << 4), make_uint4(__float_as_uint(ps[2 * i]), __float_as_uint(pq[2 * i]), __float_as_uint(ps[2 * i + 1]), __float_as_uint(pq[2 * i + 1])));
    bar_arrive(4, 256);
  } else {
    bar_sync(4, 256);
#pragma unroll
    for (int i = 0; i < 8; i++) {
      const uint32_t a = sa + ((i ^ (t & 7)) << 4);
      const uint4 o4 = lds128(a);
      sts128(a, make_uint4(__float_as_uint(ps[2 * i] + __uint_as_float(o4.x)), __float_as_uint(pq[2 * i] + __uint_as_float(o4.y)),
                           __float_as_uint(ps[2 * i + 1] + __uint_as_float(o4.z)), __float_as_uint(pq[2 * i + 1] + __uint_as_float(o4.w))));
    }
    fence_async_smem();
    __syncwarp();
    if (lane == 0) mbar_arrive(bar + 8 * B_STAGED);
  }
}

struct RowC { float a1[2], b1[2], r[2], rm[2]; };

struct CsV { float2 g[2], u[2]; };
__device__ __forceinline__ void g1_ldcs(CsV& c, uint32_t csa) {
#pragma unroll
  for (int j = 0; j < 2; j++) { c.g[j] = ldsf2(csa + j * 32); c.u[j] = ldsf2(csa + 176 * 4 + j * 32); }
}
template <int NB>
__device__ __forceinline__ void g1_slice(const float (&prv)[64], const CsV& c, const RowC& rc, uint32_t* hp) {
  float e[8], u[8];
#pragma unroll
  for (int i = 0; i < 8; i++) {
    const int j = i >> 2, hh = (i >> 1) & 1;
    e[i] = 1.f + ex2f(fmaf(prv[4 * NB + i], rc.a1[hh], ((i & 1) ? c.g[j].y : c.g[j].x) * rc.b1[hh]));
    u[i] = fmaf(prv[32 + 4 * NB + i], rc.r[hh], ((i & 1) ? c.u[j].y : c.u[j].x) * rc.rm[hh]);
  }
#pragma unroll
  for (int i = 0; i < 4; i++) hp[(NB + (i >> 1)) * 256 + (i & 1) * 32] = pack_bf(u[2 * i] * rcpf(e[2 * i]), u[2 * i + 1] * rcpf(e[2 * i + 1]));
}

struct Ring { uint32_t st, ph; };
template <int NV, bool XW>
__device__ __forceinline__ void g1_mma2(float (&acc)[64], uint32_t bar, uint32_t da, uint32_t dw, int kb, int sc0, bool rel, const Ring& rg, int layer) {
#pragma unroll
  for (int h = 0; h < 2; h++) {
    if (XW) mbar_wait(bar + 8 * B_XFULL + 8 * (kb + h), layer);
    mbar_wait(bar + 8 * B_WFULL + 8 * (rg.st + h), rg.ph);
    const uint32_t a = da + (kb + h) * 1024, b = dw + (rg.st + h) * 1024;
    wg_fence();
#pragma unroll
    for (int k = 0; k < 4; k++) {
      if (NV == 0) wg_g1_n128(acc, a + k * 128, b + k * 128, (h | k) ? 1 : sc0);
      else wg_g1_n112(acc, a + k * 128, b + k * 128, (h | k) ? 1 : sc0);
    }
    wg_commit();
    if (h == 0) {
      wg_wait<1>();
      if (rel) mbar_arrive(bar + 8 * B_WEMPTY + 8 * (rg.st ? rg.st - 1 : 5));
    }
  }
}
__device__ __forceinline__ void g1_release(uint32_t bar, bool l0, Ring& rg) {
  wg_wait<1>();
  if (l0) mbar_arrive(bar + 8 * B_WEMPTY + 8 * rg.st);
  rg.st += 2;
  if (rg.st == 6) { rg.st = 0; rg.ph ^= 1; }
}

struct G1Tail { RowC rc; uint32_t csa; uint32_t* hp; };

__device__ __forceinline__ void gemm1_phase(const Params& p, uint32_t sb, int layer, int w, int wp, int lane, int ti, int tj,
                                            float (&accA)[64], float (&accB)[64], G1Tail& tl) {
  const uint32_t bar = sb + SM_BAR;
  const bool l0 = lane == 0;
#pragma unroll
  for (int i = 0; i < 64; i++) { accA[i] = 0.f; accB[i] = 0.f; }
  pin_regs(accA); pin_regs(accB);
  const uint32_t dx = desc_lo(sb + SM_X + w * 8192, 1024), dw = desc_lo(sb + SM_WR, 8192);
  Ring rg; rg.st = 0; rg.ph = 0;
#pragma unroll 1
  for (int kb = 0; kb < 4; kb += 2) {
    g1_mma2<0, true>(accA, bar, dx, dw, kb, kb, l0 && kb > 0, rg, layer);
    g1_release(bar, l0, rg);
  }
#pragma unroll 1
  for (int kb = 0; kb < 4; kb += 2) {
    g1_mma2<0, false>(accB, bar, dx, dw, kb, kb, l0, rg, layer);
    g1_release(bar, l0, rg);
  }
#pragma unroll 1
  for (int kb = 4; kb < 8; kb += 2) {
    g1_mma2<0, true>(accA, bar, dx, dw, kb, 1, l0, rg, layer);
    g1_release(bar, l0, rg);
  }
  RowC& rc = tl.rc;
  uint32_t* hp = reinterpret_cast<uint32_t*>(p.sc->h) + ((2 * ti + w) * 24 + tj) * 2048 + 2 * wp * 32 + lane;
  const uint32_t csa = sb + SM_CS + 2 * (lane & 3) * 4;
  mbar_wait(bar + 8 * B_STFULL, layer);
  if (layer == 0) mbar_wait(bar + 8 * B_CSFULL, 0);
#pragma unroll
  for (int hh = 0; hh < 2; hh++) {
    const float2 mr = ldsf2(sb + SM_ST + (w * 64 + 16 * wp + (lane >> 2) + 8 * hh) * 8);
    rc.a1[hh] = -1.4426950408889634f * mr.y; rc.b1[hh] = 1.4426950408889634f * mr.y * mr.x;
    rc.r[hh] = mr.y; rc.rm[hh] = -mr.y * mr.x;
  }
  if (w == 1) bar_sync(6, 256);
#define G1_IT(ACC, SRC, NV, KB, SC0, NB, CS, HP, FIRST)                        \
  {                                                                            \
    CsV c, c2;                                                                 \
    g1_ldcs(c, (CS) + (NB) * 32);                                              \
    g1_mma2<NV, false>(ACC, bar, dx, dw, KB, SC0, l0, rg, 0);                  \
    if (FIRST) { pin_regs(SRC); if (w == 0) bar_arrive(6, 256); }              \
    g1_ldcs(c2, (CS) + (NB) * 32 + 64);                                        \
    g1_slice<NB>(SRC, c, rc, HP);                                              \
    g1_slice<NB + 2>(SRC, c2, rc, HP);                                         \
    g1_release(bar, l0, rg);                                                   \
  }
  G1_IT(accB, accA, 0, 4, 1, 0, csa, hp, true)
  G1_IT(accB, accA, 0, 6, 1, 4, csa, hp, false)
  __syncwarp();
  if (l0) mbar_arrive(bar + 8 * (B_PUB + 2 * w));
  if (w == 1) bar_sync(6, 256);
  G1_IT(accA, accB, 1, 0, 0, 0, csa + 256, hp + 8 * 2048, true)
  G1_IT(accA, accB, 1, 2, 1, 4, csa + 256, hp + 8 * 2048, false)
#undef G1_IT
  __syncwarp();
  if (l0) mbar_arrive(bar + 8 * (B_PUB + 2 * w + 1));
#pragma unroll 1
  for (int kb = 4; kb < 8; kb += 2) {
    g1_mma2<1, false>(accA, bar, dx, dw, kb, 1, l0, rg, 0);
    g1_release(bar, l0, rg);
  }
  wg_wait<0>();
  pin_regs(accA);
  if (l0) { mbar_arrive(bar + 8 * B_WEMPTY + 8 * 5); mbar_arrive(bar + 8 * B_G1DONE); }
  tl.csa = csa + 512;
  tl.hp = hp + 16 * 2048;
}

__device__ __forceinline__ void gemm2_phase(const Params& p, uint32_t sb, int layer, int w, int wp, int lane, int tt, int tq,
                                            int tj, const float (&prv)[64], const G1Tail& tl) {
  const uint32_t bar = sb + SM_BAR;
  const int t = wp * 32 + lane;
  {
    CsV c0, c1, c2;
    g1_ldcs(c0, tl.csa); g1_ldcs(c1, tl.csa + 64); g1_ldcs(c2, tl.csa + 128);
    g1_slice<0>(prv, c0, tl.rc, tl.hp);
    if (tj < 7) { g1_slice<2>(prv, c1, tl.rc, tl.hp); g1_slice<4>(prv, c2, tl.rc, tl.hp); }
    __syncwarp();
    if (lane == 0) mbar_arrive(bar + 8 * (B_PUB + 2 * w));
  }
  float acc[32];
#pragma unroll
  for (int i = 0; i < 32; i++) acc[i] = 0.f;
  pin_regs(acc);
  uint32_t stage = 0, phase = (layer * 3) & 1;
#pragma unroll 1
  for (int n = 0; n < 12; n++) {
    mbar_wait(bar + 8 * (B_G2FULL + stage), phase);
    const uint32_t sa = sb + g2_stage_off(stage);
    const uint32_t da = desc_lo(sa + w * (n < 8 ? 8192 : 6144), 1024), db = desc_lo(sa + 32768, 1024);
    if (n < 8) {
      wg_fence();
#pragma unroll
      for (int k = 0; k < 4; k++) wg_g2_n64(acc, da + k * 128, db + k * 128, (n | k) != 0);
#pragma unroll
      for (int k = 0; k < 4; k++) wg_g2_n64(acc, da + 1024 + k * 128, db + 512 + k * 128, 1);
      wg_commit();
    } else if (n < 11) {
      wg_fence();
#pragma unroll
      for (int k = 0; k < 3; k++) wg_g2_n64(acc, da + k * 128, db + k * 128, 1);
#pragma unroll
      for (int k = 0; k < 3; k++) wg_g2_n64(acc, da + 1024 + k * 128, db + 512 + k * 128, 1);
      wg_commit();
    } else {
      wg_fence();
#pragma unroll
      for (int k = 0; k < 3; k++) wg_g2_n64(acc, da + k * 128, db + k * 128, 1);
      wg_g2_n64(acc, da + 1024, db + 512, 1);
      wg_commit();
    }
    wg_wait<1>();
    if (n > 0 && lane == 0) mbar_arrive(bar + 8 * (B_G2EMPTY + ((stage + 3) & 3)));
    if (++stage == 4) { stage = 0; phase ^= 1; }
  }
  wg_wait<0>();
  pin_regs(acc);
  if (lane == 0) mbar_arrive(bar + 8 * (B_G2EMPTY + 3));
  mbar_wait(bar + 8 * B_RESFULL, layer);
  const int g = lane >> 2, c = lane & 3;
  const int mat = lane >> 3;
  const int rrow = 64 * w + 16 * wp + (lane & 7) + 8 * (mat & 1);
  const int rk = 2 * (rrow >> 2) + (rrow & 1);
  const uint32_t ra = sb + SM_RES + ((rrow >> 1) & 1) * 8192 + rk * 128;
  uint32_t o[16];
#pragma unroll
  for (int nb = 0; nb < 8; nb += 2) {
    uint32_t r0, r1, r2, r3;
    ldsm4(ra + (((nb + (mat >> 1)) ^ (rk & 7)) << 4), r0, r1, r2, r3);
    const uint32_t rr[4] = {r0, r1, r2, r3};
#pragma unroll
    for (int k = 0; k < 4; k++) {
      const int a = 4 * (nb + (k >> 1)) + 2 * (k & 1);
      o[2 * nb + k] = bf2_add(rr[k], pack_bf(acc[a], acc[a + 1]));
    }
  }
  if (layer == 0) {
#pragma unroll
    for (int nb = 0; nb < 8; nb += 2)
      stsm4(ra + (((nb + (mat >> 1)) ^ (rk & 7)) << 4), o[2 * nb], o[2 * nb + 1], o[2 * nb + 2], o[2 * nb + 3]);
    __syncwarp();
#pragma unroll
    for (int i = 0; i < 4; i++) {
      const int idx = lane + 32 * i, row = 64 * w + 16 * wp + (idx >> 3), ch = idx & 7;
      const int k2 = 2 * (row >> 2) + (row & 1);
      const uint4 v = lds128(sb + SM_RES + ((row >> 1) & 1) * 8192 + k2 * 128 + ((ch ^ (k2 & 7)) << 4));
      *reinterpret_cast<uint4*>(p.sc->xT[1] + (128 * tq + row) * SEQ + 64 * tt + 8 * ch) = v;
    }
    float v[32];
#pragma unroll
    for (int nb = 0; nb < 8; nb++) {
      const uint32_t a = o[2 * (nb & ~1) + 2 * (nb & 1)], b = o[2 * (nb & ~1) + 2 * (nb & 1) + 1];
      const float a0 = bf_lo(a), a1 = bf_hi(a), b0 = bf_lo(b), b1 = bf_hi(b);
      v[4 * nb] = a0 + b0; v[4 * nb + 1] = a1 + b1;
      v[4 * nb + 2] = fmaf(a0, a0, b0 * b0); v[4 * nb + 3] = fmaf(a1, a1, b1 * b1);
    }
    const bool s4 = lane & 16, s3 = lane & 8, s2 = lane & 4;
#pragma unroll
    for (int i = 0; i < 16; i++) {
      const float snd = s4 ? v[i] : v[16 + i], kp = s4 ? v[16 + i] : v[i];
      v[i] = kp + __shfl_xor_sync(0xffffffffu, snd, 16);
    }
#pragma unroll
    for (int i = 0; i < 8; i++) {
      const float snd = s3 ? v[i] : v[8 + i], kp = s3 ? v[8 + i] : v[i];
      v[i] = kp + __shfl_xor_sync(0xffffffffu, snd, 8);
    }
#pragma unroll
    for (int i = 0; i < 4; i++) {
      const float snd = s2 ? v[i] : v[4 + i], kp = s2 ? v[4 + i] : v[i];
      v[i] = kp + __shfl_xor_sync(0xffffffffu, snd, 4);
    }
    {
      const int nbf = (s4 ? 4 : 0) + (s3 ? 2 : 0) + (s2 ? 1 : 0), col = 8 * nbf + 2 * c;
      const uint32_t scr = sb + SM_G2S + (w * 4 + wp) * 512 + col * 8;
      stsf2(scr, v[0], v[2]);
      stsf2(scr + 8, v[1], v[3]);
    }
    bar_sync(4, 256);
    if (w == 0) {
      float s = 0.f;
#pragma unroll
      for (int k = 0; k < 8; k++) s += ldsf(sb + SM_G2S + k * 512 + t * 4);
      atomicAdd(reinterpret_cast<float*>(p.sc->stat3) + 128 * tt + t, s);
    }
    __syncwarp();
    if (lane == 0) mbar_arrive(bar + 8 * (B_PUB + 2 * w + 1));
    fence_async_smem();
    __syncwarp();
    if (lane == 0) mbar_arrive(bar + 8 * B_G2DONE);
  } else {
    const uint32_t oa = sb + SM_G2S + w * 8192;
#pragma unroll
    for (int nb = 0; nb < 8; nb += 2) {
      const int l = 8 * (nb + (mat >> 1)) + (lane & 7), chunk = 2 * wp + (mat & 1);
      stsm4t(oa + l * 128 + ((chunk ^ (l & 7)) << 4), o[2 * nb], o[2 * nb + 1], o[2 * nb + 2], o[2 * nb + 3]);
    }
    bar_sync(1 + w, 128);
#pragma unroll
    for (int i = 0; i < 4; i++) {
      const int idx = t + 128 * i, l = idx >> 3, ch = idx & 7;
      const uint4 v = lds128(oa + l * 128 + ((ch ^ (l & 7)) << 4));
      *reinterpret_cast<uint4*>(p.out + (64 * tt + l) * DM + 128 * tq + 64 * w + 8 * ch) = v;
    }
  }
  (void)g;
}

__global__ void __launch_bounds__(NTHR, 1)
fused_s4d_glu_kernel(const __grid_constant__ CUtensorMap tmG, const __grid_constant__ CUtensorMap tmU, const __grid_constant__ CUtensorMap tmWd,
                     const __grid_constant__ CUtensorMap tmWd48, const __grid_constant__ CUtensorMap tmCG,
                     const __grid_constant__ CUtensorMap tmCU, const Params p) {
  extern __shared__ __align__(1024) unsigned char smem[];
  const uint32_t sb = smem_u32(smem);
  const uint32_t bar = sb + SM_BAR;
  const int tid = threadIdx.x, lane = tid & 31;
  const int warp = __shfl_sync(0xffffffffu, tid >> 5, 0);
  const int cta = blockIdx.x;
  const int grp = cta >> 4, r16 = cta & 15;
  const int ti = 4 * (grp & 3) + (r16 & 3), tj = 4 * (grp >> 2) + (r16 >> 2);
  const int tt = 4 * grp + (r16 >> 2), tq = r16 & 3;
  uint32_t kraw[10];
  if (warp < 8) {
#pragma unroll
    for (int v = 0; v < 2; v++) {
      const int ch = 4 * cta + 2 * v + (warp >> 2), idx = ch * NMODE + (tid & 127);
      asm volatile("ld.global.nc.u16 %0, [%1];" : "=r"(kraw[5 * v]) : "l"(p.logA + idx));
      asm volatile("ld.global.nc.u16 %0, [%1];" : "=r"(kraw[5 * v + 1]) : "l"(p.Aim + idx));
      asm volatile("ld.global.nc.u16 %0, [%1];" : "=r"(kraw[5 * v + 2]) : "l"(p.Cre + idx));
      asm volatile("ld.global.nc.u16 %0, [%1];" : "=r"(kraw[5 * v + 3]) : "l"(p.Cim + idx));
      asm volatile("ld.global.nc.u16 %0, [%1];" : "=r"(kraw[5 * v + 4]) : "l"(p.logdt + ch));
    }
  }
  uint4 xrow[8];
  if (warp >= 8) {
#pragma unroll
    for (int r = 0; r < 4; r++) {
      const bf16* src = p.x0 + (16 * cta + 4 * (warp - 8) + r) * DM + lane * 8;
      xrow[2 * r] = ldg128_nc(src); xrow[2 * r + 1] = ldg128_nc(src + 256);
    }
  }
  if (warp >= 8 && lane == 0) {
    if (sb & 1023) __trap();
    const uint32_t codes = warp == 8 ? (uint32_t)LO_CODES : (warp == 9 ? (uint32_t)(LO_CODES >> 32) : (warp == 10 ? (uint32_t)HI_CODES : (uint32_t)(HI_CODES >> 32)));
    const uint32_t b0 = bar + (warp - 8) * 128;
#pragma unroll
    for (int i = 0; i < 16; i++) mbar_init(b0 + 8 * i, 1u << ((codes >> (2 * i)) & 3));
    asm volatile("fence.mbarrier_init.release.cluster;" ::: "memory");
  }
  __syncthreads();

  if (warp < 8) {
    asm volatile("setmaxnreg.inc.sync.aligned.u32 224;");
    const int w = warp >> 2, wp = warp & 3;
    KParam kp[2];
#pragma unroll
    for (int v = 0; v < 2; v++) {
      uint32_t f[5];
#pragma unroll
      for (int k = 0; k < 5; k++) asm volatile("shl.b32 %0, %1, 16;" : "=r"(f[k]) : "r"(kraw[5 * v + k]));
      kp[v].logA = __uint_as_float(f[0]); kp[v].aim = __uint_as_float(f[1]); kp[v].cre = __uint_as_float(f[2]);
      kp[v].cim = __uint_as_float(f[3]); kp[v].logdt = __uint_as_float(f[4]);
    }
    float kinv[2];
    kgen(sb, w, wp, lane, kp, kinv, p.x0 + 8 * tid * DM + 4 * cta);
#pragma unroll 1
    for (int layer = 0; layer < 2; layer++) {
      conv_phase(p, sb, layer, w, wp, lane, cta, kinv[0], kinv[1]);
      float accA[64], accB[64];
      G1Tail tl;
      gemm1_phase(p, sb, layer, w, wp, lane, ti, tj, accA, accB, tl);
      gemm2_phase(p, sb, layer, w, wp, lane, tt, tq, tj, accA, tl);
    }
    __syncwarp();
    if (lane == 0) mbar_arrive(bar + 8 * B_KDONE);
  } else {
    asm volatile("setmaxnreg.dec.sync.aligned.u32 56;");
    const int wv = warp - 8;
    unsigned ep1;
    asm volatile("ld.relaxed.gpu.global.u32 %0, [%1];" : "=r"(ep1) : "l"(&p.sc->epoch) : "memory");
    ep1 += 1;
    {
      uint4 (&v)[8] = xrow;
      if (lane < 9) {
        float2* z = (lane == 0 ? p.sc->stat3 : p.sc->stat2[(lane - 1) >> 2][(lane - 1) & 3]) + 16 * cta + 4 * wv;
        *reinterpret_cast<uint4*>(z) = make_uint4(0, 0, 0, 0);
        *reinterpret_cast<uint4*>(z + 2) = make_uint4(0, 0, 0, 0);
      }
      float a[8];
#pragma unroll
      for (int r = 0; r < 4; r++) {
        const uint32_t xx[8] = {v[2 * r].x, v[2 * r].y, v[2 * r].z, v[2 * r].w, v[2 * r + 1].x, v[2 * r + 1].y, v[2 * r + 1].z, v[2 * r + 1].w};
        float s0 = 0.f, s1 = 0.f, q0 = 0.f, q1 = 0.f;
#pragma unroll
        for (int k = 0; k < 8; k++) { const float lo = bf_lo(xx[k]), hi = bf_hi(xx[k]); s0 += lo; s1 += hi; q0 = fmaf(lo, lo, q0); q1 = fmaf(hi, hi, q1); }
        a[2 * r] = s0 + s1; a[2 * r + 1] = q0 + q1;
      }
      const bool s4 = lane & 16, s3 = lane & 8, s2 = lane & 4;
#pragma unroll
      for (int i = 0; i < 4; i++) { const float snd = s4 ? a[i] : a[4 + i], kp2 = s4 ? a[4 + i] : a[i]; a[i] = kp2 + __shfl_xor_sync(0xffffffffu, snd, 16); }
#pragma unroll
      for (int i = 0; i < 2; i++) { const float snd = s3 ? a[i] : a[2 + i], kp2 = s3 ? a[2 + i] : a[i]; a[i] = kp2 + __shfl_xor_sync(0xffffffffu, snd, 8); }
      { const float snd = s2 ? a[0] : a[1], kp2 = s2 ? a[1] : a[0]; a[0] = kp2 + __shfl_xor_sync(0xffffffffu, snd, 4); }
      a[0] += __shfl_xor_sync(0xffffffffu, a[0], 2);
      a[0] += __shfl_xor_sync(0xffffffffu, a[0], 1);
      if ((lane & 3) == 0) reinterpret_cast<float*>(p.sc->stat1)[2 * (16 * cta + 4 * wv) + (lane >> 2)] = a[0];
      bar_sync(3, 128);
    }
    if (wv == 3) {
      if (elect_one()) {
        mbar_wait(bar + 8 * B_KGDONE, 0);
        const int njob = cta < 32 ? 3 : 2;
#pragma unroll 1
        for (int i = 0; i < njob; i++) {
          const int job = cta + 128 * i;
          const uint32_t buf = sb + SM_X + 32768 + (i & 1) * 16384, fb = bar + 8 * (B_RT + (i & 1));
          if (i == 2) asm volatile("cp.async.bulk.wait_group.read 1;" ::: "memory");
          const uint32_t rbytes = job >= 192 && (job - 192) % 24 >= 16 ? 12288 : 16384;
          mbar_expect(fb, rbytes);
          if (job < 192) {
            const int cj = job / 24, n = job - 24 * cj;
            const int pp = n < 16 ? (n >> 2) & 1 : 2, kb = n < 16 ? (n & 3) + ((n >> 1) & 4) : n - 16;
            tma_4d(buf, &tmG, 176 * cj + 64 * pp, 0, kb >> 2, 32 * (kb & 3), fb);
            tma_4d(buf + 8192, &tmU, 176 * cj + 64 * pp, 0, kb >> 2, 32 * (kb & 3), fb);
          } else {
            const int cq = (job - 192) / 24, blk = job - 192 - 24 * cq;
            tma_3d(buf, blk < 16 ? &tmWd : &tmWd48, 0, 176 * (blk & 7) + 64 * (blk >> 3), 2 * cq, fb);
          }
          if (i == 0) continue;
#pragma unroll 1
          for (int k = (i == 1 ? 0 : 2); k <= i; k++) {
            mbar_wait(bar + 8 * (B_RT + (k & 1)), k >> 1);
            const int jb = cta + 128 * k;
            bf16* dst = jb < 192 ? p.sc->wt + jb * 8192 : p.sc->wdt + (jb - 192) * 8192;
            const uint32_t sbytes = jb >= 192 && (jb - 192) % 24 >= 16 ? 12288 : 16384;
            asm volatile("cp.async.bulk.global.shared::cta.bulk_group [%0], [%1], %2;" ::"l"(dst), "r"(sb + SM_X + 32768 + (k & 1) * 16384), "r"(sbytes) : "memory");
            asm volatile("cp.async.bulk.commit_group;" ::: "memory");
          }
        }
        asm volatile("cp.async.bulk.wait_group 0;" ::: "memory");
        mbar_arrive(bar + 8 * B_RTDONE);
        fence_async_all();
        flag_publish(&p.sc->flag[F_W * 8]);
        mbar_wait(bar + 8 * B_PTDONE, 0);
        asm volatile("cp.async.bulk.global.shared::cta.bulk_group [%0], [%1], %2;" ::"l"(p.sc->ptab + 4 * cta * PTW), "r"(sb + SM_PT), "n"(4 * PTW * 4) : "memory");
        asm volatile("cp.async.bulk.commit_group;" ::: "memory");
        asm volatile("cp.async.bulk.wait_group 0;" ::: "memory");
        fence_async_all();
        mbar_arrive(bar + 8 * B_PTSAVED);
      }
      __syncwarp();
      if (elect_one()) {
        mbar_wait(bar + 8 * B_CSDONE, 0);
        flag_wait(&p.sc->flag[F_CS * 8], ep1 * 172);
        fence_async_all();
        const uint32_t fb = bar + 8 * B_CSFULL;
        const uint32_t cb = tj < 7 ? 704 : 576;
        mbar_expect(fb, 2 * cb);
        bulk_g2s(sb + SM_CS, p.sc->cs + 176 * tj, cb, fb);
        bulk_g2s(sb + SM_CS + 704, p.sc->cs + CSP + 176 * tj, cb, fb);
      }
      __syncwarp();
#pragma unroll 1
      for (int layer = 0; layer < 2; layer++) {
        if (elect_one()) {
          mbar_wait(bar + 8 * B_STAGED, layer);
          fence_async_all();
          asm volatile("cp.reduce.async.bulk.global.shared::cta.bulk_group.add.f32 [%0], [%1], 16384;" ::"l"(p.sc->stat2[layer][cta & 3]), "r"(sb + SM_MISC) : "memory");
          asm volatile("cp.async.bulk.commit_group;" ::: "memory");
          asm volatile("cp.async.bulk.wait_group.read 0;" ::: "memory");
          mbar_arrive(bar + 8 * B_TAILDONE);
          asm volatile("cp.async.bulk.wait_group 0;" ::: "memory");
          fence_async_all();
          flag_publish(&p.sc->flag[(F_S + layer) * 8]);
          flag_wait(&p.sc->flag[(F_S + layer) * 8], ep1 * 128);
        }
        __syncwarp();
#pragma unroll 1
        for (int k0 = 0; k0 < 4; k0 += 2) {
          float2 v[8];
#pragma unroll
          for (int k = 0; k < 2; k++) {
            const int l = 128 * ti + 32 * (k0 + k) + lane, tq16 = l >> 4;
            const float* src = reinterpret_cast<const float*>(p.sc->stat2[layer]) + tq16 * 32 + ((((l & 15) >> 1) ^ (tq16 & 7)) << 2) + (l & 1) * 2;
#pragma unroll
            for (int r = 0; r < 4; r++) asm volatile("ld.global.cg.v2.f32 {%0, %1}, [%2];" : "=f"(v[4 * k + r].x), "=f"(v[4 * k + r].y) : "l"(src + r * 2 * SEQ) : "memory");
          }
#pragma unroll
          for (int k = 0; k < 2; k++) {
            const float2 mr = ln_finalize((v[4 * k].x + v[4 * k + 1].x) + (v[4 * k + 2].x + v[4 * k + 3].x), (v[4 * k].y + v[4 * k + 1].y) + (v[4 * k + 2].y + v[4 * k + 3].y));
            stsf2(sb + SM_ST + (32 * (k0 + k) + lane) * 8, mr.x, mr.y);
          }
        }
        __syncwarp();
        if (lane == 0) mbar_arrive(bar + 8 * B_STFULL);
      }
      if (lane == 0) mbar_wait_checked(bar + 8 * B_KDONE, 0);
    } else if (wv == 1 || wv == 2) {
      const int unit = cta + 128 * (wv - 1);
      if (unit < 172) {
        const int mat = unit / 86, col0 = (unit - mat * 86) * 16;
        const uint32_t buf = sb + SM_X + (wv - 1) * 16384, lb = bar + 8 * (B_CSL + wv - 1);
        if (elect_one()) {
          mbar_wait(bar + 8 * B_KGDONE, 0);
          mbar_expect(lb, 16384);
          tma_2d(buf, mat ? &tmCU : &tmCG, col0, 0, lb);
          tma_2d(buf + 8192, mat ? &tmCU : &tmCG, col0, 256, lb);
        }
        __syncwarp();
        mbar_wait(lb, 0);
        float a[8];
#pragma unroll
        for (int k = 0; k < 8; k++) a[k] = 0.f;
#pragma unroll 4
        for (int i = 0; i < 32; i++) {
          const uint4 v = lds128(buf + i * 512 + lane * 16);
          a[0] += bf_lo(v.x); a[1] += bf_hi(v.x); a[2] += bf_lo(v.y); a[3] += bf_hi(v.y);
          a[4] += bf_lo(v.z); a[5] += bf_hi(v.z); a[6] += bf_lo(v.w); a[7] += bf_hi(v.w);
        }
#pragma unroll
        for (int k = 0; k < 8; k++)
#pragma unroll
          for (int o = 2; o < 32; o <<= 1) a[k] += __shfl_xor_sync(0xffffffffu, a[k], o);
        if (lane < 2) {
          float4* dst = reinterpret_cast<float4*>(p.sc->cs + mat * CSP + col0 + lane * 8);
          dst[0] = make_float4(a[0], a[1], a[2], a[3]);
          dst[1] = make_float4(a[4], a[5], a[6], a[7]);
        }
        __syncwarp();
        if (elect_one()) flag_publish(&p.sc->flag[F_CS * 8]);
        __syncwarp();
      }
      if (lane == 0) mbar_arrive(bar + 8 * B_CSDONE);
      __syncwarp();
      if (elect_one()) {
        const int w = wv - 1;
#pragma unroll 1
        for (int layer = 0; layer < 2; layer++) {
#pragma unroll 1
          for (int e = 0; e < (layer == 0 ? 6 : 5); e++) {
            mbar_wait(bar + 8 * (B_PUB + 2 * w + (e & 1)), (3 * layer + (e >> 1)) & 1);
            const int f = e < 2 ? F_1 + layer * 2 + e : (e < 5 ? F_2 + layer * 96 + (2 * ti + w) * 3 + (e - 2) : F_3);
            flag_publish(&p.sc->flag[f * 8]);
            if (e == 5) mbar_arrive(bar + 8 * B_PUB3);
          }
        }
      }
    } else if (elect_one()) {
      flag_publish(&p.sc->flag[F_0 * 8]);
      tmap_prefetch(&tmG); tmap_prefetch(&tmU); tmap_prefetch(&tmWd);
      uint32_t wst = 0, wph = 1;
      auto issue_w = [&](int n) {
        mbar_wait(bar + 8 * (B_WEMPTY + wst), wph);
        const uint32_t fb = bar + 8 * (B_WFULL + wst), dst = sb + SM_WR + wst * 16384;
        mbar_expect(fb, 16384);
        bulk_g2s(dst, p.sc->wt + (tj * 24 + n) * 8192, 16384, fb);
        if (++wst == 6) { wst = 0; wph ^= 1; }
      };
#pragma unroll 1
      for (int layer = 0; layer < 2; layer++) {
        const bf16* xin = p.sc->xT[layer ? 2 : 0];
        {
          flag_wait(&p.sc->flag[(layer ? F_3 : F_0) * 8], ep1 * (layer ? 256 : 128));
          fence_async_all();
          const uint32_t fb = bar + 8 * B_XSFULL;
          if (layer == 0) {
            if (cta == 0) asm volatile("st.relaxed.gpu.global.u32 [%0], %1;" ::"l"(&p.sc->epoch), "r"(ep1) : "memory");
            mbar_wait(bar + 8 * B_KGDONE, 0);
            mbar_expect(fb, 16384);
          } else {
            mbar_expect(fb, 32768);
            bulk_g2s(sb + CV_XS, p.sc->xT[1] + 4 * cta * SEQ, 16384, fb);
          }
          bulk_g2s(sb + CV_B97, layer ? p.sc->stat3 : p.sc->stat1, 16384, fb);
          if (layer == 0) {
            flag_wait(&p.sc->flag[F_W * 8], ep1 * 128);
            fence_async_all();
            issue_w(0);
          } else {
            mbar_wait(fb, 1);
            const uint32_t pb = bar + 8 * B_PTFULL;
            mbar_expect(pb, 4 * PTW * 4);
            bulk_g2s(sb + SM_PT, p.sc->ptab + 4 * cta * PTW, 4 * PTW * 4, pb);
            issue_w(0);
          }
          issue_w(1);
          issue_w(2);
        }
        if (layer == 0) { mbar_wait(bar + 8 * B_CSDONE, 0); mbar_wait(bar + 8 * B_RTDONE, 0); }
#pragma unroll 1
        for (int b = 0; b < 2; b++) {
          if (b == 1) {
            mbar_wait(bar + 8 * B_CONVDONE, layer);
            if (layer == 0) mbar_wait(bar + 8 * B_PTSAVED, 0);
            issue_w(3);
            issue_w(4);
            mbar_wait(bar + 8 * B_TAILDONE, layer);
            issue_w(5);
            issue_w(6);
            issue_w(7);
          }
          flag_wait(&p.sc->flag[(F_1 + layer * 2 + b) * 8], ep1 * 256);
          fence_async_all();
#pragma unroll 1
          for (int k = 0; k < 4; k++) {
            const uint32_t fb = bar + 8 * (B_XFULL + 4 * b + k);
            mbar_expect(fb, 16384);
            bulk_g2s(sb + SM_X + (4 * b + k) * 16384, xin + (ti * 8 + 4 * b + k) * 8192, 16384, fb);
          }
        }
#pragma unroll 1
        for (int n = 8; n < 24; n++) issue_w(n);
        uint32_t st2 = 0, ph2 = ((layer * 3) & 1) ^ 1;
        const bf16* hsrc = p.sc->h + tt * 24 * 4096;
        const unsigned* f2 = &p.sc->flag[(F_2 + layer * 96 + tt * 3) * 8];
        flag_wait(f2, ep1 * 8);
        fence_async_all();
#pragma unroll 1
        for (int n = 0; n < 12; n++) {
          const int pp = n >> 2, j = 2 * (n & 3);
          const uint32_t fb = bar + 8 * (B_G2FULL + st2), dst = sb + g2_stage_off(st2);
          if (n == 0) mbar_wait(bar + 8 * (B_WEMPTY + 0), 1);
          if (n == 1) { mbar_wait(bar + 8 * (B_WEMPTY + 1), 1); mbar_wait(bar + 8 * (B_WEMPTY + 2), 1); }
          if (n == 2) mbar_wait(bar + 8 * (B_WEMPTY + 3), 1);
          if (n == 3) { mbar_wait(bar + 8 * B_G1DONE, layer); }
          if (j == 0 && pp > 0) { flag_wait(f2 + pp * 8, ep1 * 8); fence_async_all(); }
          mbar_wait(bar + 8 * (B_G2EMPTY + st2), ph2);
          if (pp < 2) {
            mbar_expect(fb, 49152);
            bulk_g2s(dst, p.sc->wdt + (tq * 24 + 2 * n) * 8192, 32768, fb);
            bulk_g2s(dst + 32768, hsrc + n * 8192, 16384, fb);
          } else {
            const uint32_t h1 = j < 6 ? 6144 : 2048;
            mbar_expect(fb, 24576 + 6144 + h1);
            bulk_g2s(dst, p.sc->wdt + (tq * 24 + 2 * n) * 8192, 12288, fb);
            bulk_g2s(dst + 16384, p.sc->wdt + (tq * 24 + 2 * n + 1) * 8192, 12288, fb);
            bulk_g2s(dst + 32768, hsrc + n * 8192, 6144, fb);
            bulk_g2s(dst + 40960, hsrc + n * 8192 + 4096, h1, fb);
          }
          if (n == 3) {
            const uint32_t rb = bar + 8 * B_RESFULL;
            mbar_expect(rb, 16384);
            bulk_g2s(sb + SM_RES, xin + (((tt >> 1) * 8 + tq) * 2 + (tt & 1)) * 4096, 8192, rb);
            bulk_g2s(sb + SM_RES + 8192, xin + (((tt >> 1) * 8 + 4 + tq) * 2 + (tt & 1)) * 4096, 8192, rb);
          }
          if (++st2 == 4) { st2 = 0; ph2 ^= 1; }
        }
        if (layer == 0) { mbar_wait(bar + 8 * B_G2DONE, 0); mbar_wait(bar + 8 * B_PUB3, 0); }
      }
    }
  }
}

typedef CUresult (*EncodeFn)(CUtensorMap*, CUtensorMapDataType, cuuint32_t, void*, const cuuint64_t*, const cuuint64_t*, const cuuint32_t*,
                             const cuuint32_t*, CUtensorMapInterleave, CUtensorMapSwizzle, CUtensorMapL2promotion, CUtensorMapFloatOOBfill);

void make_map(EncodeFn fn, CUtensorMap* m, const void* base, int rank, const cuuint64_t* dims, const cuuint64_t* strides, const cuuint32_t* box) {
  cuuint32_t es[5] = {1, 1, 1, 1, 1};
  fn(m, CU_TENSOR_MAP_DATA_TYPE_BFLOAT16, rank, const_cast<void*>(base), dims, strides, box, es, CU_TENSOR_MAP_INTERLEAVE_NONE,
     CU_TENSOR_MAP_SWIZZLE_128B, CU_TENSOR_MAP_L2_PROMOTION_L2_128B, CU_TENSOR_MAP_FLOAT_OOB_FILL_NONE);
}

}

extern "C" void kernel_launch(void* const* d_in, const int* in_sizes, int n_in, void* d_out, int out_size) {
  (void)in_sizes; (void)n_in; (void)out_size;
  static EncodeFn enc = nullptr;
  static Scratch* sc = nullptr;
  if (!enc) {
    void* fn = nullptr;
    cudaDriverEntryPointQueryResult qr;
    cudaGetDriverEntryPoint("cuTensorMapEncodeTiled", &fn, cudaEnableDefault, &qr);
    enc = (EncodeFn)fn;
    void* a = nullptr;
    cudaGetSymbolAddress(&a, g_scratch);
    sc = (Scratch*)a;
    cudaFuncSetAttribute(fused_s4d_glu_kernel, cudaFuncAttributeMaxDynamicSharedMemorySize, SM_TOTAL);
  }
  Params p;
  p.x0 = (const bf16*)d_in[0]; p.logA = (const bf16*)d_in[1]; p.Aim = (const bf16*)d_in[2]; p.Cre = (const bf16*)d_in[3];
  p.Cim = (const bf16*)d_in[4]; p.logdt = (const bf16*)d_in[5]; p.Dsk = (const bf16*)d_in[6];
  p.wg = (const bf16*)d_in[8]; p.wu = (const bf16*)d_in[9]; p.wd = (const bf16*)d_in[10];
  p.out = (bf16*)d_out;
  p.sc = sc;

  CUtensorMap tmG, tmU, tmWd, tmWd48, tmCG, tmCU;
  {
    const cuuint64_t dims[4] = {FF, 2, 2, 128}, str[3] = {FF * 2, FF * 4, FF * 8};
    const cuuint32_t box[4] = {64, 2, 1, 32};
    make_map(enc, &tmG, p.wg, 4, dims, str, box);
    make_map(enc, &tmU, p.wu, 4, dims, str, box);
  }
  {
    const cuuint64_t dims[3] = {64, FF, 8}, str[2] = {DM * 2, 128};
    const cuuint32_t box[3] = {64, 64, 2};
    make_map(enc, &tmWd, p.wd, 3, dims, str, box);
    const cuuint32_t box48[3] = {64, 48, 2};
    make_map(enc, &tmWd48, p.wd, 3, dims, str, box48);
  }
  {
    const cuuint64_t dims[2] = {FF, DM}, str[1] = {FF * 2};
    const cuuint32_t box[2] = {16, 256}, es[2] = {1, 1};
    enc(&tmCG, CU_TENSOR_MAP_DATA_TYPE_BFLOAT16, 2, const_cast<bf16*>(p.wg), dims, str, box, es, CU_TENSOR_MAP_INTERLEAVE_NONE,
        CU_TENSOR_MAP_SWIZZLE_NONE, CU_TENSOR_MAP_L2_PROMOTION_L2_128B, CU_TENSOR_MAP_FLOAT_OOB_FILL_NONE);
    enc(&tmCU, CU_TENSOR_MAP_DATA_TYPE_BFLOAT16, 2, const_cast<bf16*>(p.wu), dims, str, box, es, CU_TENSOR_MAP_INTERLEAVE_NONE,
        CU_TENSOR_MAP_SWIZZLE_NONE, CU_TENSOR_MAP_L2_PROMOTION_L2_128B, CU_TENSOR_MAP_FLOAT_OOB_FILL_NONE);
  }
  fused_s4d_glu_kernel<<<NCTA, NTHR, SM_TOTAL, cudaStreamPerThread>>>(tmG, tmU, tmWd, tmWd48, tmCG, tmCU, p);
}
```
